```python
import torch

def _softmax(x, axis=-1):
    return torch.softmax(x, dim=axis)
def _gelu(x):
    return torch.nn.functional.gelu(x, approximate="tanh")
def _silu(x):
    return torch.nn.functional.silu(x)
def _sigmoid(x):
    return torch.sigmoid(x)
def _layernorm(x, axis=-1, eps=1e-5):
    m = x.mean(dim=axis, keepdim=True)
    v = x.var(dim=axis, keepdim=True, unbiased=False)
    return (x - m) / torch.sqrt(v + eps)
def _scatter_add(tgt, idx, src, axis=0):
    return tgt.clone().index_add_(axis, idx, src)
def _segment_sum(src, seg, n):
    out = torch.zeros((n,) + src.shape[1:], dtype=src.dtype)
    return out.index_add_(0, seg, src)
def _pad(x, pw):
    flat = tuple(v for pair in reversed(pw) for v in pair)
    return torch.nn.functional.pad(x, flat)

kernel_name = 'gather_scatter__edge_featured_mpnn_mpnn__graph'

def setup_inputs():

    _w = (lambda a: (lambda t: t.to(torch.bfloat16) if t.is_floating_point() else t)(torch.as_tensor(a)))
    N, deg, D, De = 12500, 64, 64, max(0, 1)
    E = N * deg
    H = 2 * D
    return {
        "x": _w((lambda *s: torch.randn(*s, dtype=torch.bfloat16) * 0.05)(N, D)),
        "e_attr": _w((lambda *s: torch.randn(*s, dtype=torch.bfloat16) * 1.6)(E, De)),
        "src": _w((lambda lo, hi, *s: torch.randint(lo, hi, s))(0, N, E).to(torch.int64)),
        "dst": _w((lambda lo, hi, *s: torch.randint(lo, hi, s))(0, N, E).to(torch.int64)),
        "w1": _w((lambda *s: torch.randn(*s, dtype=torch.bfloat16) * 1.6)(2 * D + De, H) * (1.0 / (2 * D + De) ** 0.5)),
        "b1": _w((lambda *s: torch.randn(*s, dtype=torch.bfloat16) * 1.6)(H) * 0.01),
        "w2": _w((lambda *s: torch.randn(*s, dtype=torch.bfloat16) * 0.05)(H, D) * (1.0 / H ** 0.5)),
        "b2": _w((lambda *s: torch.randn(*s, dtype=torch.bfloat16) * 0.05)(D) * 0.01),
    }

def reference(x, e_attr, src, dst, w1, b1, w2, b2):
    N, D = x.shape
    h_src = x[src]
    h_dst = x[dst]
    m_in = torch.concatenate([h_src, h_dst, e_attr], axis=-1)
    h = _silu(m_in @ w1 + b1)
    msg = h @ w2 + b2
    return _segment_sum(msg, dst, N)
```

```cpp
#include <cuda_runtime.h>
#include <cuda_bf16.h>
#include <stdint.h>

namespace {

constexpr int N_NODES = 12500;
constexpr int N_EDGES = 800000;
constexpr int GRID    = 132;
constexpr int THREADS = 1024;
constexpr int NWARPS  = THREADS / 32;
constexpr int NPB     = 95;
constexpr int CHUNK   = 6064;
constexpr int EIT     = 3;
constexpr int LPC     = 7;
constexpr int RIT     = 6;
constexpr int CAPN    = GRID * LPC * RIT * 2;
constexpr int CAPS    = CAPN / 2 + NPB + 13;
constexpr uint32_t NULLREC = N_NODES;
constexpr int SPIN_MAX = 1 << 22;
static_assert(GRID * CHUNK >= N_EDGES && (GRID - 1) * CHUNK < N_EDGES && CHUNK % 2 == 0, "chunking");
static_assert(EIT * THREADS * 2 >= CHUNK && GRID * LPC <= THREADS && GRID * NPB >= N_NODES, "coverage");
static_assert(N_EDGES - (GRID - 1) * CHUNK >= (EIT - 1) * THREADS * 2, "only the last load is predicated");
static_assert(CAPN >= CHUNK && CAPS % 8 == 4, "list capacity");

constexpr int SM_X     = 0;
constexpr int SM_W1    = SM_X + 96 * 128;
constexpr int SM_W2    = SM_W1 + 4 * 8192;
constexpr int SM_AGG   = SM_W2 + 128 * 128;
constexpr int SM_CARRY = SM_AGG + 2 * 96 * 128;
constexpr int SM_STAGE = SM_AGG;
constexpr int SM_Q     = SM_STAGE + CHUNK * 8;
constexpr int SM_LIST  = SM_Q + 96 * 320;
constexpr int SM_HIST  = SM_LIST + CAPS * 8;
constexpr int SM_CNT   = SM_HIST + 160 * 4;
constexpr int SM_DEG   = SM_CNT + 96 * 4;
constexpr int SM_FLAG  = SM_DEG + 96 * 4;
constexpr int SM_NST   = SM_FLAG + 32 * 4;
constexpr int SM_NSTEP = SM_NST + 96 * 4;
constexpr int SM_SEG   = SM_NSTEP + 96 * 4;
constexpr int SM_WE    = SM_SEG + GRID * 4;
constexpr int SM_B1    = SM_WE + 256;
constexpr int SM_B2    = SM_B1 + 256;
constexpr int SM_EPOCH = SM_B2 + 128;
constexpr int SM_TOTAL = SM_EPOCH + 16;
static_assert(SM_CARRY + 32 * 512 <= SM_Q && SM_TOTAL <= 232448, "smem");
static_assert(SM_W1 % 1024 == 0 && SM_AGG % 1024 == 0 && SM_Q % 128 == 0 && SM_LIST % 16 == 0 && SM_WE % 16 == 0, "alignment");

__device__ uint4    g_P[(N_NODES + 1) * 16];
__device__ uint4    g_rec[GRID * CHUNK / 2];
__device__ uint4    g_tab[GRID * GRID * 2];
__device__ float    g_outacc[N_NODES * 64];
__device__ __align__(16) unsigned g_epoch[4];
__device__ unsigned g_pcnt;
#define TS(i)

__device__ __forceinline__ void cp16(uint32_t dst, const void* src) {
    asm volatile("cp.async.cg.shared.global [%0], [%1], 16;" :: "r"(dst), "l"(src) : "memory");
}
__device__ __forceinline__ uint2 ld_stream2(const void* p) {
    uint2 v;
    asm volatile("ld.global.L1::no_allocate.v2.u32 {%0,%1}, [%2];" : "=r"(v.x), "=r"(v.y) : "l"(p) : "memory");
    return v;
}
__device__ __forceinline__ uint32_t ld_stream1(const void* p) {
    uint32_t v;
    asm volatile("ld.global.L1::no_allocate.u32 %0, [%1];" : "=r"(v) : "l"(p) : "memory");
    return v;
}
__device__ __forceinline__ uint4 ld_relaxed(const uint4* p) {
    unsigned long long a, b;
    asm volatile("ld.relaxed.gpu.global.v2.u64 {%0,%1}, [%2];" : "=l"(a), "=l"(b) : "l"(p) : "memory");
    return make_uint4((uint32_t)a, (uint32_t)(a >> 32), (uint32_t)b, (uint32_t)(b >> 32));
}
__device__ __forceinline__ uint2 ld_relaxed(const uint2* p) {
    unsigned long long a;
    asm volatile("ld.relaxed.gpu.global.u64 %0, [%1];" : "=l"(a) : "l"(p) : "memory");
    return make_uint2((uint32_t)a, (uint32_t)(a >> 32));
}
__device__ __forceinline__ void st_relaxed(uint4* p, uint4 v) {
    const unsigned long long a = v.x | ((unsigned long long)v.y << 32), b = v.z | ((unsigned long long)v.w << 32);
    asm volatile("st.relaxed.gpu.global.v2.u64 [%0], {%1,%2};" :: "l"(p), "l"(a), "l"(b) : "memory");
}
__device__ __forceinline__ uint4 ld_gather(const char* base, uint32_t rec) {
    uint4 v;
    asm volatile("{.reg .u64 a; .reg .u32 r; and.b32 r, %5, 0xFFFF; mad.wide.u32 a, r, 256, %4;\n"
                 "ld.global.L1::no_allocate.v4.u32 {%0,%1,%2,%3}, [a];}"
                 : "=r"(v.x), "=r"(v.y), "=r"(v.z), "=r"(v.w) : "l"(base), "r"(rec));
    return v;
}
__device__ __forceinline__ uint64_t desc_sw128(uint32_t saddr) {
    return (uint64_t)((saddr & 0x3FFFF) >> 4) | ((uint64_t)1 << 16) | ((uint64_t)64 << 32) | ((uint64_t)1 << 62);
}
__device__ __forceinline__ void wgmma_ss(float (&d)[32], uint64_t da, uint64_t db) {
    asm volatile("{.reg .pred p; setp.ne.b32 p, 1, 0;\n"
                 "wgmma.mma_async.sync.aligned.m64n64k16.f32.bf16.bf16 {%0,%1,%2,%3,%4,%5,%6,%7,%8,%9,%10,%11,%12,%13,%14,%15,%16,%17,%18,%19,%20,%21,%22,%23,%24,%25,%26,%27,%28,%29,%30,%31}, %32, %33, p, 1, 1, 0, 1;}"
                 : "+f"(d[0]), "+f"(d[1]), "+f"(d[2]), "+f"(d[3]), "+f"(d[4]), "+f"(d[5]), "+f"(d[6]), "+f"(d[7]), "+f"(d[8]), "+f"(d[9]), "+f"(d[10]), "+f"(d[11]), "+f"(d[12]), "+f"(d[13]), "+f"(d[14]), "+f"(d[15]), "+f"(d[16]), "+f"(d[17]), "+f"(d[18]), "+f"(d[19]), "+f"(d[20]), "+f"(d[21]), "+f"(d[22]), "+f"(d[23]), "+f"(d[24]), "+f"(d[25]), "+f"(d[26]), "+f"(d[27]), "+f"(d[28]), "+f"(d[29]), "+f"(d[30]), "+f"(d[31])
                 : "l"(da), "l"(db));
}
__device__ __forceinline__ void wgmma_ss(float (&d)[16], uint64_t da, uint64_t db) {
    asm volatile("{.reg .pred p; setp.ne.b32 p, 1, 0;\n"
                 "wgmma.mma_async.sync.aligned.m64n32k16.f32.bf16.bf16 {%0,%1,%2,%3,%4,%5,%6,%7,%8,%9,%10,%11,%12,%13,%14,%15}, %16, %17, p, 1, 1, 0, 1;}"
                 : "+f"(d[0]), "+f"(d[1]), "+f"(d[2]), "+f"(d[3]), "+f"(d[4]), "+f"(d[5]), "+f"(d[6]), "+f"(d[7]), "+f"(d[8]), "+f"(d[9]), "+f"(d[10]), "+f"(d[11]), "+f"(d[12]), "+f"(d[13]), "+f"(d[14]), "+f"(d[15])
                 : "l"(da), "l"(db));
}
template <int K> __device__ __forceinline__ void wgmma_begin(float (&d)[K]) {
#pragma unroll
    for (int i = 0; i < K; i++) asm volatile("" : "+f"(d[i]) :: "memory");
    asm volatile("wgmma.fence.sync.aligned;" ::: "memory");
}
template <int K> __device__ __forceinline__ void wgmma_end(float (&d)[K]) {
    asm volatile("wgmma.commit_group.sync.aligned;" ::: "memory");
    asm volatile("wgmma.wait_group.sync.aligned 0;" ::: "memory");
#pragma unroll
    for (int i = 0; i < K; i++) asm volatile("" : "+f"(d[i]) :: "memory");
}
__device__ __forceinline__ void fence_async() { asm volatile("fence.proxy.async.shared::cta;" ::: "memory"); }
__device__ __forceinline__ uint32_t half_bf16x2(uint32_t v) {
    uint32_t r;
    asm("mul.rn.bf16x2 %0, %1, %2;" : "=r"(r) : "r"(v), "r"(0x3F003F00u));
    return r;
}
__device__ __forceinline__ uint32_t pack_bf16(float lo, float hi) {
    uint32_t r;
    asm("cvt.rn.bf16x2.f32 %0, %1, %2;" : "=r"(r) : "f"(hi), "f"(lo));
    return r;
}
__device__ __forceinline__ float silu_from_half(float h) {
    float t;
    asm("tanh.approx.f32 %0, %1;" : "=f"(t) : "f"(h));
    return fmaf(h, t, h);
}
__device__ __forceinline__ uint32_t fma_hi(uint32_t a, uint32_t b, uint32_t c) {
    uint32_t r;
    asm("{.reg .b16 l, h; .reg .b32 t; mov.b32 {l, h}, %1; mov.b32 t, {h, h}; fma.rn.bf16x2 %0, t, %2, %3;}"
        : "=r"(r) : "r"(a), "r"(b), "r"(c));
    return r;
}
__device__ __forceinline__ uint32_t prmt(uint32_t a, uint32_t b, uint32_t s) {
    uint32_t r;
    asm("prmt.b32 %0, %1, %2, %3;" : "=r"(r) : "r"(a), "r"(b), "r"(s));
    return r;
}
__device__ __forceinline__ float bf_lo(uint32_t v) { return __uint_as_float(v << 16); }
__device__ __forceinline__ float bf_hi(uint32_t v) { return __uint_as_float(v & 0xFFFF0000u); }
__device__ __forceinline__ uint32_t list_off(uint32_t v) { return v + (v & 2u) * (CAPS * 2 - 1); }
__device__ __forceinline__ void put_rec(unsigned char* smem, uint32_t v, uint32_t rec) {
    *reinterpret_cast<uint32_t*>(smem + SM_LIST + list_off(v)) = rec;
}

__device__ __forceinline__ void scan_nodes(unsigned char* smem, int lane) {
    int* cnt = reinterpret_cast<int*>(smem + SM_CNT);
    int c[3], st[3], s = 0;
#pragma unroll
    for (int q = 0; q < 3; q++) {
        c[q] = cnt[lane * 3 + q];
        st[q] = (lane * 3 + q < NPB) ? max(1, (c[q] + 2) >> 2) : 0;
        s += st[q];
    }
    int inc = s;
#pragma unroll
    for (int o = 1; o < 32; o <<= 1) {
        const int v = __shfl_up_sync(0xffffffffu, inc, o);
        if (lane >= o) inc += v;
    }
    const int total = __shfl_sync(0xffffffffu, inc, 31);
    inc -= s;
#pragma unroll
    for (int q = 0; q < 3; q++) {
        const int n = lane * 3 + q;
        reinterpret_cast<int*>(smem + SM_NST)[n] = inc * 4;
        reinterpret_cast<int*>(smem + SM_NSTEP)[n] = n < NPB ? st[q] : (1 << 28);
        reinterpret_cast<int*>(smem + SM_DEG)[n] += c[q] >> 1;
        if (c[q] < st[q] * 4) put_rec(smem, (inc + st[q]) * 4 - 2, NULLREC);
        if (c[q] == 0) put_rec(smem, inc * 4, NULLREC);
        inc += st[q];
    }
    if (lane < 24) put_rec(smem, total * 4 + lane * 2, NULLREC);
}

__device__ __forceinline__ void run_round(unsigned char* smem, const char* __restrict__ ptab, uint32_t half_hi,
                                          __nv_bfloat16* __restrict__ out, bool first_round, bool last_round) {
    const uint32_t sb = (uint32_t)__cvta_generic_to_shared(smem);
    const int lane = threadIdx.x & 31, warp = __shfl_sync(0xffffffffu, threadIdx.x >> 5, 0);
    const int hf = lane >> 4, cl = lane & 15;
    const int* nst = reinterpret_cast<const int*>(smem + SM_NST);
    const int n0 = nst[lane * 3], n1 = nst[lane * 3 + 1], n2 = nst[lane * 3 + 2];
    const int total4 = __reduce_max_sync(0xffffffffu, n2);
    const int groups = (total4 + 12) >> 4;
    const int base = groups / NWARPS, ex = groups % NWARPS;
    int left = base + (warp < ex ? 1 : 0);
    if (left > 0) {
        const int o0 = (warp * base + min(warp, ex)) * 16, o1 = o0 + left * 16;
        const uint4* lp = reinterpret_cast<const uint4*>(smem + SM_LIST + hf * (CAPS * 4) + o0);
        const char* pb = ptab + cl * 16;
        uint4 ra = lp[0];
        uint4 p0 = ld_gather(pb, ra.x), p1 = ld_gather(pb, ra.y);
        int node = __reduce_add_sync(0xffffffffu, (n0 <= o0) + (n1 <= o0) + (n2 <= o0)) - 1;
        int rem = (__reduce_min_sync(0xffffffffu, n0 > o0 ? n0 : n1 > o0 ? n1 : n2 > o0 ? n2 : total4) - o0) >> 2;
        bool head_split = !__any_sync(0xffffffffu, n0 == o0 || n1 == o0 || n2 == o0);
        const bool tail_split = o1 < total4 && !__any_sync(0xffffffffu, n0 == o1 || n1 == o1 || n2 == o1);
        uint32_t we[4], q[4];
#pragma unroll
        for (int i = 0; i < 4; i++) we[i] = half_bf16x2(reinterpret_cast<const uint32_t*>(smem + SM_WE)[(cl >> 2) * 16 + i * 4 + (cl & 3)]);
        float acc[8];
        uint32_t qa = sb + SM_Q + node * 320 + cl * 16;
        auto next_node = [&]() {
            asm volatile("ld.shared.v4.u32 {%0,%1,%2,%3}, [%4];" : "=r"(q[0]), "=r"(q[1]), "=r"(q[2]), "=r"(q[3]) : "r"(qa));
            qa += 320;
#pragma unroll
            for (int i = 0; i < 8; i++) acc[i] = 0.f;
        };
        auto store_node = [&](bool add_carry) {
            float o[4];
#pragma unroll
            for (int i = 0; i < 4; i++)
                o[i] = (hf ? acc[4 + i] : acc[i]) + __shfl_xor_sync(0xffffffffu, hf ? acc[i] : acc[4 + i], 16);
            if (add_carry) {
                int f = 0;
                for (int spin = 0; !f && spin < SPIN_MAX; spin++)
                    asm volatile("ld.acquire.cta.shared.u32 %0, [%1];" : "=r"(f) : "r"(sb + SM_FLAG + warp * 4 + 4) : "memory");
                const float4 c = *reinterpret_cast<const float4*>(smem + SM_CARRY + (threadIdx.x + 32) * 16);
                o[0] += c.x; o[1] += c.y; o[2] += c.z; o[3] += c.w;
            }
            if (head_split) {
                *reinterpret_cast<float4*>(smem + SM_CARRY + threadIdx.x * 16) = make_float4(o[0], o[1], o[2], o[3]);
                __syncwarp();
                asm volatile("st.release.cta.shared.u32 [%0], 1;" :: "r"(sb + SM_FLAG + warp * 4) : "memory");
                head_split = false;
            } else {
                asm volatile("st.shared.v2.u32 [%0], {%1,%2};" :: "r"(sb + SM_AGG + (cl >> 3) * (96 * 128) + hf * 8 + node * 128 + (((cl ^ node) & 7) << 4)),
                             "r"(pack_bf16(o[0], o[1])), "r"(pack_bf16(o[2], o[3])) : "memory");
            }
        };
        auto step = [&](uint4& p, uint32_t rec, uint32_t nxt, int d) {
            const uint32_t pv[4] = {p.x, p.y, p.z, p.w};
            uint32_t z[4];
#pragma unroll
            for (int i = 0; i < 4; i++) z[i] = fma_hi(half_hi, pv[i], fma_hi(rec, we[i], q[i]));
            p = ld_gather(pb, nxt);
#pragma unroll
            for (int i = 0; i < 4; i++) {
                acc[2 * i]     += silu_from_half(__uint_as_float(prmt(z[i], 0, 0x1044)));
                acc[2 * i + 1] += silu_from_half(bf_hi(z[i]));
            }
            if (__builtin_expect(rem == d + 1, 0)) {
                store_node(false);
                node++;
                int ns;
                asm volatile("ld.shared.u32 %0, [%1];" : "=r"(ns) : "r"(sb + SM_NSTEP + node * 4));
                rem += __reduce_max_sync(0xffffffffu, ns);
                next_node();
            }
        };
        next_node();
        while (true) {
            const uint4 rb = lp[1];
            step(p0, ra.x, ra.z, 0); step(p1, ra.y, ra.w, 1); step(p0, ra.z, rb.x, 2); step(p1, ra.w, rb.y, 3);
            if (left == 1) break;
            ra = lp[2];
            step(p0, rb.x, rb.z, 4); step(p1, rb.y, rb.w, 5); step(p0, rb.z, ra.x, 6); step(p1, rb.w, ra.y, 7);
            lp += 2; rem -= 8; left -= 2;
            if (left == 0) break;
        }
        if (tail_split) store_node(true);
    }
    fence_async();
    __syncthreads();
    TS(6);
    if (warp < 16) {
        const int mh = (warp >> 2) & 1, nh = warp >> 3, g = lane >> 2, t = lane & 3;
        float d[16];
#pragma unroll
        for (int i = 0; i < 16; i++) d[i] = 0.f;
        const uint64_t da = desc_sw128(sb + SM_AGG + mh * 8192), db = desc_sw128(sb + SM_W2 + nh * 64);
        wgmma_begin(d);
#pragma unroll
        for (int s = 0; s < 8; s++) wgmma_ss(d, da + (s >> 2) * (96 * 8) + (s & 3) * 2, db + s * 128);
        uint32_t bv[4];
#pragma unroll
        for (int j = 0; j < 4; j++) bv[j] = reinterpret_cast<const uint32_t*>(smem + SM_B2)[nh * 16 + j * 4 + t];
        const int r0 = (warp & 7) * 16 + g, rows = min(NPB, N_NODES - (int)blockIdx.x * NPB);
        const int o = (blockIdx.x * NPB + r0) * 64 + nh * 32 + t * 2;
        const int* deg = reinterpret_cast<const int*>(smem + SM_DEG);
        const float dg[2] = {(float)deg[min(r0, NPB)], (float)deg[min(r0 + 8, NPB)]};
        wgmma_end(d);
#pragma unroll
        for (int u = 0; u < 2; u++) {
            if (r0 + 8 * u < rows) {
#pragma unroll
                for (int j = 0; j < 4; j++) {
                    float v0 = d[4 * j + 2 * u], v1 = d[4 * j + 2 * u + 1];
                    float* acc = g_outacc + o + u * 512 + j * 8;
                    if (!first_round) { v0 += acc[0]; v1 += acc[1]; }
                    if (last_round) {
                        *reinterpret_cast<uint32_t*>(out + o + u * 512 + j * 8) =
                            pack_bf16(fmaf(dg[u], bf_lo(bv[j]), v0), fmaf(dg[u], bf_hi(bv[j]), v1));
                    } else {
                        acc[0] = v0; acc[1] = v1;
                    }
                }
            }
        }
    }
    TS(7);
}

__device__ __noinline__ void run_slow(unsigned char* smem, const char* ptab, uint32_t half_hi, __nv_bfloat16* out, uint32_t tag) {
    const int tid = threadIdx.x, lane = tid & 31, warp = tid >> 5;
    int* cur = reinterpret_cast<int*>(smem + SM_HIST);
    int* cnt = reinterpret_cast<int*>(smem + SM_CNT);
    const int* nst = reinterpret_cast<const int*>(smem + SM_NST);
    const uint32_t* seg = reinterpret_cast<const uint32_t*>(smem + SM_SEG);
    for (int c0 = 0; c0 < GRID;) {
        __syncthreads();
        if (tid < 160 + 96) cur[tid] = 0;
        if (tid < 32) reinterpret_cast<int*>(smem + SM_FLAG)[tid] = 0;
        int c1 = c0;
        for (int sum = 0; c1 < GRID; c1++) {
            sum += (int)(seg[c1] >> 16) - (int)(seg[c1] & 0xFFFF);
            if (sum > CAPN) break;
        }
        __syncthreads();
        for (int pass = 0; pass < 2; pass++) {
            for (int c = c0; c < c1; c++) {
                const int s = seg[c] & 0xFFFF, e = seg[c] >> 16;
                const bool wide = e - s > 256;
                if (!wide && (c & (NWARPS - 1)) != warp) continue;
                for (int i = s + (wide ? tid : lane); i < e; i += (wide ? THREADS : 32)) {
                    const uint2* p = reinterpret_cast<const uint2*>(g_rec) + c * CHUNK + i;
                    uint2 r = ld_relaxed(p);
                    for (int spin = 0; ((r.y ^ tag) >> 14) != 0 && spin < SPIN_MAX; spin++) r = ld_relaxed(p);
                    const uint32_t l = min(r.y - tag - blockIdx.x * NPB, NPB - 1u);
                    if (pass == 0) atomicAdd(&cnt[l], 2);
                    else put_rec(smem, nst[l] + atomicAdd(&cur[l], 2), r.x);
                }
            }
            __syncthreads();
            if (pass == 0) {
                if (warp == 0) scan_nodes(smem, lane);
                __syncthreads();
            }
        }
        run_round(smem, ptab, half_hi, out, c0 == 0, c1 >= GRID);
        c0 = c1;
    }
}

template <int PHASES>
__global__ void __launch_bounds__(THREADS, 1)
mpnn_kernel(const __nv_bfloat16* __restrict__ x, const unsigned short* __restrict__ e_attr,
            const int* __restrict__ src, const int* __restrict__ dst,
            const __nv_bfloat16* __restrict__ w1, const void* __restrict__ b1,
            const __nv_bfloat16* __restrict__ w2, const void* __restrict__ b2,
            __nv_bfloat16* __restrict__ out, const char* __restrict__ ptab, uint32_t half_hi) {
    if (PHASES == 4) { if (threadIdx.x == 0) g_epoch[0] = g_epoch[0] + 1; return; }
    extern __shared__ __align__(1024) unsigned char smem[];
    const uint32_t sb = (uint32_t)__cvta_generic_to_shared(smem);
    const int tid = threadIdx.x, lane = tid & 31;
    const int warp = __shfl_sync(0xffffffffu, tid >> 5, 0);
    const int cta = blockIdx.x;
    int* hist = reinterpret_cast<int*>(smem + SM_HIST);
    TS(0);

    uint2 vd[EIT], vs[EIT];
    uint32_t ve[EIT];
    const int e0 = cta * CHUNK + tid * 2;
    const bool tail_ok = tid * 2 + (EIT - 1) * THREADS * 2 < CHUNK && e0 + (EIT - 1) * THREADS * 2 < N_EDGES;
    {
        const uint32_t dw = sb + SM_W1 + ((tid >> 3) & 1) * 8192 + (tid >> 4) * 128 + (((tid ^ (tid >> 4)) & 7) << 4);
        cp16(dw, w1 + tid * 8);
        cp16(dw + 16384, w1 + tid * 8 + 64 * 128);
        if (tid < 96 * 8) cp16(sb + SM_X + (tid >> 3) * 128 + (((tid ^ (tid >> 3)) & 7) << 4), x + min(cta * (NPB * 64) + tid * 8, N_NODES * 64 - 8));
        else if (tid < 96 * 8 + 41) {
            const int i = tid - 96 * 8;
            const char* p = i < 16 ? reinterpret_cast<const char*>(w1 + 128 * 128) : i < 32 ? reinterpret_cast<const char*>(b1) - 256
                          : i < 40 ? reinterpret_cast<const char*>(b2) - 512 : reinterpret_cast<const char*>(g_epoch) - 640;
            cp16(sb + SM_WE + i * 16, p + i * 16);
        }
        asm volatile("cp.async.commit_group;" ::: "memory");
    }
    if (PHASES & 1) {
        vd[EIT - 1] = make_uint2(0, 0); vs[EIT - 1] = make_uint2(0, 0); ve[EIT - 1] = 0;
#pragma unroll
        for (int j = 0; j < EIT; j++) if (j < EIT - 1 || tail_ok) vd[j] = ld_stream2(dst + e0 + j * THREADS * 2);
    }
    if (tid < 160 + 96 + 96 + 32) hist[tid] = 0;
    uint4* const my_tab = &g_tab[((tid >> 1) * GRID + cta) * 2 + (tid & 1)];
    if (PHASES & 1) {
        __syncthreads();
#pragma unroll
        for (int j = 0; j < EIT; j++) if (j < EIT - 1 || tail_ok) vs[j] = ld_stream2(src + e0 + j * THREADS * 2);
#pragma unroll
        for (int j = 0; j < EIT; j++) if (j < EIT - 1 || tail_ok) ve[j] = ld_stream1(e_attr + e0 + j * THREADS * 2);
        if (PHASES == 3 && tid < GRID * 2) st_relaxed(my_tab, make_uint4(0, 0, 0, 0));
    }
    asm volatile("cp.async.wait_group 0;" ::: "memory");
    fence_async();
    __syncthreads();
    TS(8);

    {
        const int nq = warp >> 3, g = lane >> 2, t = lane & 3;
        const int r0 = (warp & 7) * 16 + g;
        float d[32];
#pragma unroll
        for (int j = 0; j < 8; j++) {
            const uint32_t b = nq >= 2 ? reinterpret_cast<const uint32_t*>(smem + SM_B1)[(nq & 1) * 32 + j * 4 + t] : 0u;
            d[4 * j] = d[4 * j + 2] = bf_lo(b);
            d[4 * j + 1] = d[4 * j + 3] = bf_hi(b);
        }
        const uint64_t da = desc_sw128(sb + SM_X + ((warp >> 2) & 1) * 8192), db = desc_sw128(sb + SM_W1 + nq * 8192);
        wgmma_begin(d);
#pragma unroll
        for (int s = 0; s < 4; s++) wgmma_ss(d, da + s * 2, db + s * 128);
        wgmma_end(d);
        if ((warp & 7) < 6) {
            const int rows = min(NPB, N_NODES - cta * NPB);
#pragma unroll
            for (int u = 0; u < 2; u++) {
#pragma unroll
                for (int J = 0; J < 2; J++) {
                    const float* c = d + 16 * J + 2 * u;
                    const uint4 v = make_uint4(pack_bf16(c[0], c[1]), pack_bf16(c[4], c[5]), pack_bf16(c[8], c[9]), pack_bf16(c[12], c[13]));
                    if (nq >= 2)
                        *reinterpret_cast<uint4*>(smem + SM_Q + (r0 + 8 * u) * 320 + (nq & 1) * 128 + J * 64 + t * 16) =
                            make_uint4(half_bf16x2(v.x), half_bf16x2(v.y), half_bf16x2(v.z), half_bf16x2(v.w));
                    else if ((PHASES & 1) && r0 + 8 * u < rows)
                        g_P[(cta * NPB + r0 + 8 * u) * 16 + nq * 8 + J * 4 + t] = v;
                }
            }
        }
        if ((PHASES & 1) && cta == 0 && tid < 16) g_P[N_NODES * 16 + tid] = make_uint4(0xF149F149u, 0xF149F149u, 0xF149F149u, 0xF149F149u);
    }
    TS(1);
    const unsigned epoch = *reinterpret_cast<const unsigned*>(smem + SM_EPOCH);
    const uint32_t tag = ((epoch & 0xFFFFu) + 1u) << 14;

    if (PHASES & 1) {
        uint32_t bin[EIT * 2], rank[EIT * 2];
#pragma unroll
        for (int j = 0; j < EIT * 2; j++) {
            bin[j] = (((j & 1) ? vd[j >> 1].y : vd[j >> 1].x) * 44151u) >> 22;
            rank[j] = 0;
            if (j < EIT * 2 - 2 || tail_ok) rank[j] = atomicAdd(&hist[bin[j]], 1);
        }
        __syncthreads();
        TS(2);
        if (warp == 0) {
            int h[5], s = 0;
#pragma unroll
            for (int q = 0; q < 5; q++) { h[q] = hist[lane * 5 + q]; s += h[q]; }
            int inc = s;
#pragma unroll
            for (int o = 1; o < 32; o <<= 1) {
                const int v = __shfl_up_sync(0xffffffffu, inc, o);
                if (lane >= o) inc += v;
            }
            inc -= s;
#pragma unroll
            for (int q = 0; q < 5; q++) { hist[lane * 5 + q] = inc; inc += h[q]; }
        }
        __syncthreads();
        TS(9);
        uint2* stage = reinterpret_cast<uint2*>(smem + SM_STAGE);
#pragma unroll
        for (int j = 0; j < EIT * 2; j++) rank[j] += hist[bin[j]];
#pragma unroll
        for (int j = 0; j < EIT; j++) {
            if (j < EIT - 1 || tail_ok) {
                stage[rank[2 * j]]     = make_uint2(prmt(vs[j].x, ve[j], 0x5410), vd[j].x | tag);
                stage[rank[2 * j + 1]] = make_uint2(prmt(vs[j].y, ve[j], 0x7610), vd[j].y | tag);
            }
        }
        __syncthreads();
        TS(10);
#pragma unroll
        for (int j = 0; j < EIT; j++)
            if (j < EIT - 1 || tail_ok)
                st_relaxed(g_rec + cta * (CHUNK / 2) + j * THREADS + tid, *reinterpret_cast<const uint4*>(smem + SM_STAGE + (j * THREADS + tid) * 16));
        if (tid < GRID * 2) {
            const uint32_t se = hist[tid >> 1] | (hist[(tid >> 1) + 1] << 16);
            st_relaxed(my_tab, make_uint4(se, tag, se, tag));
        }
        if (PHASES == 3 && tid == THREADS - 32) asm volatile("red.release.gpu.global.add.u32 [%0], 1;" :: "l"(&g_pcnt) : "memory");
        TS(3);
    }
    if (!(PHASES & 2)) return;
    {
        const int h = tid >> 3, p = (h & 0x61) | ((h & 6) << 2) | ((h >> 2) & 6);
        cp16(sb + SM_W2 + p * 128 + (((tid ^ p) & 7) << 4), w2 + tid * 8);
        asm volatile("cp.async.commit_group;" ::: "memory");
    }

    const int c = tid / LPC, j = tid - c * LPC;
    int s = 0, e = 0;
    if (c < GRID) {
        const uint2* tp = reinterpret_cast<const uint2*>(&g_tab[(cta * GRID + c) * 2]);
        uint2 v = ld_relaxed(tp);
        for (int spin = 0; v.y != tag && spin < SPIN_MAX; spin++) v = ld_relaxed(tp);
        if (v.y != tag) v.x = 0;
        s = v.x & 0xFFFF; e = v.x >> 16;
        reinterpret_cast<uint32_t*>(smem + SM_SEG)[c] = v.x;
    }
    TS(11);
    const int npair = ((e + 1) >> 1) - (s >> 1) - j;
    const uint4* rp = g_rec + c * (CHUNK / 2) + (s >> 1) + j;
    const int kmax = __reduce_max_sync(0xffffffffu, npair);
    uint4 r[RIT];
    uint32_t rk[RIT * 2];
    for (int spin = 0; spin < SPIN_MAX; spin++) {
        uint32_t bad = 0;
#pragma unroll
        for (int k = 0; k < RIT; k++) {
            r[k].y = tag + 16383u; r[k].w = tag + 16383u;
            if (k * LPC < npair) r[k] = ld_relaxed(rp + k * LPC);
        }
#pragma unroll
        for (int k = 0; k < RIT; k++) bad |= (r[k].y ^ tag) | (r[k].w ^ tag);
        if (bad < 16384u) break;
    }
    TS(12);
    const uint32_t loc0 = tag + cta * NPB;
    auto rank_in_node = [&](uint32_t& y, uint32_t& rnk) {
        y = min(y - loc0, (uint32_t)NPB) * 4;
        asm volatile("{.reg .pred p; setp.lt.u32 p, %1, %3; @p atom.shared.add.u32 %0, [%2], 2;}"
                     : "=r"(rnk) : "r"(y), "r"(sb + SM_CNT + y), "n"(4 * NPB) : "memory");
    };
#pragma unroll
    for (int k = 0; k < RIT; k++) {
        if (k < 4 || k * LPC < kmax) { rank_in_node(r[k].y, rk[2 * k]); rank_in_node(r[k].w, rk[2 * k + 1]); }
    }
    if (PHASES == 3 && tid == THREADS - 32) {
        const unsigned target = (epoch + 1u) * GRID;
        unsigned v;
        int spin = 0;
        do {
            asm volatile("ld.acquire.gpu.global.u32 %0, [%1];" : "=r"(v) : "l"(&g_pcnt) : "memory");
        } while ((int)(v - target) < 0 && ++spin < SPIN_MAX);
        if (cta == 0) g_epoch[0] = epoch + 1u;
    }
    asm volatile("cp.async.wait_group 0;" ::: "memory");
    if (__syncthreads_or(npair + j > LPC * RIT)) {
        run_slow(smem, ptab, half_hi, out, tag);
        return;
    }
    TS(4);
    if (warp == 0) scan_nodes(smem, lane);
    __syncthreads();
#pragma unroll
    for (int k = 0; k < RIT; k++) {
        if (k < 4 || k * LPC < kmax) {
            rk[2 * k]     += *reinterpret_cast<const int*>(smem + SM_NST + r[k].y);
            rk[2 * k + 1] += *reinterpret_cast<const int*>(smem + SM_NST + r[k].w);
        }
    }
#pragma unroll
    for (int k = 0; k < RIT; k++) {
        if (k < 4 || k * LPC < kmax) {
            if (r[k].y < 4 * NPB) put_rec(smem, rk[2 * k], r[k].x);
            if (r[k].w < 4 * NPB) put_rec(smem, rk[2 * k + 1], r[k].z);
        }
    }
    __syncthreads();
    TS(5);
    run_round(smem, ptab, half_hi, out, true, true);
}

}

extern "C" void kernel_launch(void* const* d_in, const int* in_sizes, int n_in, void* d_out, int out_size) {
    (void)in_sizes; (void)n_in; (void)out_size;
    const __nv_bfloat16* x  = (const __nv_bfloat16*)d_in[0];
    const unsigned short* e = (const unsigned short*)d_in[1];
    const int* src          = (const int*)d_in[2];
    const int* dst          = (const int*)d_in[3];
    const __nv_bfloat16* w1 = (const __nv_bfloat16*)d_in[4];
    const void* b1          = d_in[5];
    const __nv_bfloat16* w2 = (const __nv_bfloat16*)d_in[6];
    const void* b2          = d_in[7];
    __nv_bfloat16* out = (__nv_bfloat16*)d_out;

    static int fused = -1;
    static void* ptab = nullptr;
    if (fused < 0) {
        cudaFuncSetAttribute(mpnn_kernel<3>, cudaFuncAttributeMaxDynamicSharedMemorySize, SM_TOTAL);
        cudaFuncSetAttribute(mpnn_kernel<1>, cudaFuncAttributeMaxDynamicSharedMemorySize, SM_TOTAL);
        cudaFuncSetAttribute(mpnn_kernel<2>, cudaFuncAttributeMaxDynamicSharedMemorySize, SM_TOTAL);
        cudaGetSymbolAddress(&ptab, g_P);
        int dev = 0, sms = 0, per_sm = 0;
        cudaGetDevice(&dev);
        cudaDeviceGetAttribute(&sms, cudaDevAttrMultiProcessorCount, dev);
        cudaOccupancyMaxActiveBlocksPerMultiprocessor(&per_sm, mpnn_kernel<3>, THREADS, SM_TOTAL);
        fused = (sms * per_sm >= GRID) ? 1 : 0;
    }
    const char* pt = (const char*)ptab;
    if (fused) {
        mpnn_kernel<3><<<GRID, THREADS, SM_TOTAL>>>(x, e, src, dst, w1, b1, w2, b2, out, pt, 0x3F000000u);
    } else {
        mpnn_kernel<1><<<GRID, THREADS, SM_TOTAL>>>(x, e, src, dst, w1, b1, w2, b2, out, pt, 0x3F000000u);
        mpnn_kernel<2><<<GRID, THREADS, SM_TOTAL>>>(x, e, src, dst, w1, b1, w2, b2, out, pt, 0x3F000000u);
        mpnn_kernel<4><<<1, 32>>>(x, e, src, dst, w1, b1, w2, b2, out, pt, 0x3F000000u);
    }
}
```

```cpp
#include <cuda_runtime.h>
#include <cuda_bf16.h>
#include <stdint.h>

namespace {

constexpr int N_NODES = 12500;
constexpr int N_EDGES = 800000;
constexpr int GRID    = 132;
constexpr int THREADS = 1024;
constexpr int NWARPS  = THREADS / 32;
constexpr int NPB     = 95;
constexpr int CHUNK   = 6064;
constexpr int EIT     = 3;
constexpr int LPC     = 7;
constexpr int RIT     = 3;
constexpr int CAPN    = GRID * LPC * RIT * 4;
constexpr int CAPS    = CAPN / 2 + NPB + 13;
constexpr uint32_t NULLREC = N_NODES;
constexpr int SPIN_MAX = 1 << 22;
static_assert(GRID * CHUNK >= N_EDGES && (GRID - 1) * CHUNK < N_EDGES && CHUNK % 16 == 0 && N_EDGES % 8 == 0 && CHUNK * 5 <= THREADS * 32, "chunking");
static_assert(EIT * THREADS * 2 >= CHUNK && GRID * LPC <= THREADS - 32 && GRID * NPB >= N_NODES, "coverage");
static_assert(N_EDGES - (GRID - 1) * CHUNK >= (EIT - 1) * THREADS * 2, "only the last load is predicated");
static_assert(CAPN >= CHUNK && CAPS % 8 == 4, "list capacity");

constexpr int SM_X     = 0;
constexpr int SM_W1    = SM_X + 96 * 128;
constexpr int SM_W2    = SM_W1 + 4 * 8192;
constexpr int SM_AGG   = SM_W2 + 128 * 128;
constexpr int SM_CARRY = SM_AGG + 2 * 96 * 128;
constexpr int SM_STAGE = SM_AGG;
constexpr int SM_Q     = SM_CARRY + 32 * 512;
constexpr int SM_LIST  = SM_Q + 96 * 320;
constexpr int SM_HIST  = SM_LIST + CAPS * 8;
constexpr int SM_CNT   = SM_HIST + 160 * 4;
constexpr int SM_DEG   = SM_CNT + 96 * 4;
constexpr int SM_FLAG  = SM_DEG + 96 * 4;
constexpr int SM_NST   = SM_FLAG + 32 * 4;
constexpr int SM_NSTEP = SM_NST + 96 * 4;
constexpr int SM_SEG   = SM_NSTEP + 96 * 4;
constexpr int SM_WE    = SM_SEG + GRID * 4;
constexpr int SM_B2    = SM_WE + 256;
constexpr int SM_B1    = SM_B2 + 128;
constexpr int SM_EPOCH = SM_B1 + 512;
constexpr int SM_MBAR  = SM_EPOCH + 8;
constexpr int SM_SRC   = SM_MBAR + 8;
constexpr int SM_E     = SM_SRC + CHUNK * 4;
constexpr int SM_TOTAL = SM_E + CHUNK * 2;
static_assert(SM_STAGE + CHUNK * 5 <= SM_Q && SM_TOTAL <= 232448, "smem");
static_assert(SM_W1 % 1024 == 0 && SM_AGG % 1024 == 0 && SM_Q % 128 == 0 && SM_LIST % 16 == 0 && CHUNK * 6 >= 96 * 256 && SM_WE % 16 == 0 && SM_SRC % 16 == 0, "alignment");

__device__ uint4    g_P[(N_NODES + 1) * 16];
__device__ uint4    g_rec[GRID * (CHUNK * 5 / 16)];
__device__ uint4    g_tab[GRID * GRID * 2];
__device__ float    g_outacc[N_NODES * 64];
__device__ unsigned g_epoch[1];
__device__ unsigned g_pcnt;
#define TS(i)

__device__ __forceinline__ void cp16(uint32_t dst, const void* src) {
    asm volatile("cp.async.cg.shared.global [%0], [%1], 16;" :: "r"(dst), "l"(src) : "memory");
}
__device__ __forceinline__ uint2 ld_stream2(const void* p) {
    uint2 v;
    asm volatile("ld.global.L1::no_allocate.v2.u32 {%0,%1}, [%2];" : "=r"(v.x), "=r"(v.y) : "l"(p) : "memory");
    return v;
}
__device__ __forceinline__ uint32_t ld_stream1(const void* p) {
    uint32_t v;
    asm volatile("ld.global.L1::no_allocate.u32 %0, [%1];" : "=r"(v) : "l"(p) : "memory");
    return v;
}
__device__ __forceinline__ uint4 ld_relaxed(const uint4* p) {
    unsigned long long a, b;
    asm volatile("ld.relaxed.gpu.global.v2.u64 {%0,%1}, [%2];" : "=l"(a), "=l"(b) : "l"(p) : "memory");
    return make_uint4((uint32_t)a, (uint32_t)(a >> 32), (uint32_t)b, (uint32_t)(b >> 32));
}
__device__ __forceinline__ uint2 ld_relaxed(const uint2* p) {
    unsigned long long a;
    asm volatile("ld.relaxed.gpu.global.u64 %0, [%1];" : "=l"(a) : "l"(p) : "memory");
    return make_uint2((uint32_t)a, (uint32_t)(a >> 32));
}
__device__ __forceinline__ uint32_t ld_relaxed(const uint32_t* p) {
    uint32_t a;
    asm volatile("ld.relaxed.gpu.global.u32 %0, [%1];" : "=r"(a) : "l"(p) : "memory");
    return a;
}
__device__ __forceinline__ uint32_t tag_rec(uint32_t tag) { return (tag & 0x4000u) ? 0x4000u : 0x8000u; }
__device__ __forceinline__ uint32_t tag_dst(uint32_t tag) { return (tag & 0x4000u) ? 0x80808080u : 0u; }
__device__ __forceinline__ void st_relaxed(uint4* p, uint4 v) {
    const unsigned long long a = v.x | ((unsigned long long)v.y << 32), b = v.z | ((unsigned long long)v.w << 32);
    asm volatile("st.relaxed.gpu.global.v2.u64 [%0], {%1,%2};" :: "l"(p), "l"(a), "l"(b) : "memory");
}
__device__ __forceinline__ uint4 ld_gather(const char* base, uint32_t rec) {
    uint4 v;
    asm volatile("{.reg .u64 a; .reg .u32 r; and.b32 r, %5, 0x3FFF; mad.wide.u32 a, r, 256, %4;\n"
                 "ld.global.L1::no_allocate.v4.u32 {%0,%1,%2,%3}, [a];}"
                 : "=r"(v.x), "=r"(v.y), "=r"(v.z), "=r"(v.w) : "l"(base), "r"(rec));
    return v;
}
__device__ __forceinline__ uint64_t desc_sw128(uint32_t saddr) {
    return (uint64_t)((saddr & 0x3FFFF) >> 4) | ((uint64_t)1 << 16) | ((uint64_t)64 << 32) | ((uint64_t)1 << 62);
}
__device__ __forceinline__ void wgmma_ss(float (&d)[32], uint64_t da, uint64_t db, int accumulate) {
    asm volatile("{.reg .pred p; setp.ne.b32 p, %34, 0;\n"
                 "wgmma.mma_async.sync.aligned.m64n64k16.f32.bf16.bf16 {%0,%1,%2,%3,%4,%5,%6,%7,%8,%9,%10,%11,%12,%13,%14,%15,%16,%17,%18,%19,%20,%21,%22,%23,%24,%25,%26,%27,%28,%29,%30,%31}, %32, %33, p, 1, 1, 0, 1;}"
                 : "+f"(d[0]), "+f"(d[1]), "+f"(d[2]), "+f"(d[3]), "+f"(d[4]), "+f"(d[5]), "+f"(d[6]), "+f"(d[7]), "+f"(d[8]), "+f"(d[9]), "+f"(d[10]), "+f"(d[11]), "+f"(d[12]), "+f"(d[13]), "+f"(d[14]), "+f"(d[15]), "+f"(d[16]), "+f"(d[17]), "+f"(d[18]), "+f"(d[19]), "+f"(d[20]), "+f"(d[21]), "+f"(d[22]), "+f"(d[23]), "+f"(d[24]), "+f"(d[25]), "+f"(d[26]), "+f"(d[27]), "+f"(d[28]), "+f"(d[29]), "+f"(d[30]), "+f"(d[31])
                 : "l"(da), "l"(db), "r"(accumulate));
}
template <int K> __device__ __forceinline__ void wgmma_begin(float (&d)[K]) {
#pragma unroll
    for (int i = 0; i < K; i++) asm volatile("" : "+f"(d[i]) :: "memory");
    asm volatile("wgmma.fence.sync.aligned;" ::: "memory");
}
template <int K> __device__ __forceinline__ void wgmma_end(float (&d)[K]) {
    asm volatile("wgmma.commit_group.sync.aligned;" ::: "memory");
    asm volatile("wgmma.wait_group.sync.aligned 0;" ::: "memory");
#pragma unroll
    for (int i = 0; i < K; i++) asm volatile("" : "+f"(d[i]) :: "memory");
}
__device__ __forceinline__ void fence_async() { asm volatile("fence.proxy.async.shared::cta;" ::: "memory"); }
__device__ __forceinline__ uint32_t half_bf16x2(uint32_t v) {
    uint32_t r;
    asm("mul.rn.bf16x2 %0, %1, %2;" : "=r"(r) : "r"(v), "r"(0x3F003F00u));
    return r;
}
__device__ __forceinline__ uint32_t pack_bf16(float lo, float hi) {
    uint32_t r;
    asm("cvt.rn.bf16x2.f32 %0, %1, %2;" : "=r"(r) : "f"(hi), "f"(lo));
    return r;
}
__device__ __forceinline__ float silu_from_half(float h) {
    float t;
    asm("tanh.approx.f32 %0, %1;" : "=f"(t) : "f"(h));
    return fmaf(h, t, h);
}
__device__ __forceinline__ uint32_t fma_hi(uint32_t a, uint32_t b, uint32_t c) {
    uint32_t r;
    asm("{.reg .b16 l, h; .reg .b32 t; mov.b32 {l, h}, %1; mov.b32 t, {h, h}; fma.rn.bf16x2 %0, t, %2, %3;}"
        : "=r"(r) : "r"(a), "r"(b), "r"(c));
    return r;
}
__device__ __forceinline__ uint32_t prmt(uint32_t a, uint32_t b, uint32_t s) {
    uint32_t r;
    asm("prmt.b32 %0, %1, %2, %3;" : "=r"(r) : "r"(a), "r"(b), "r"(s));
    return r;
}
__device__ __forceinline__ float bf_lo(uint32_t v) { return __uint_as_float(v << 16); }
__device__ __forceinline__ float bf_hi(uint32_t v) { return __uint_as_float(v & 0xFFFF0000u); }
__device__ __forceinline__ uint32_t list_off(uint32_t v) { return v + (v & 2u) * (CAPS * 2 - 1); }
__device__ __forceinline__ void put_rec(unsigned char* smem, uint32_t v, uint32_t rec) {
    *reinterpret_cast<uint32_t*>(smem + SM_LIST + list_off(v)) = rec;
}

__device__ __forceinline__ void scan_nodes(unsigned char* smem, int lane) {
    int* cnt = reinterpret_cast<int*>(smem + SM_CNT);
    int c[3], st[3], s = 0;
#pragma unroll
    for (int q = 0; q < 3; q++) {
        c[q] = cnt[lane * 3 + q];
        st[q] = (lane * 3 + q < NPB) ? max(1, (c[q] + 2) >> 2) : 0;
        s += st[q];
    }
    int inc = s;
#pragma unroll
    for (int o = 1; o < 32; o <<= 1) {
        const int v = __shfl_up_sync(0xffffffffu, inc, o);
        if (lane >= o) inc += v;
    }
    const int total = __shfl_sync(0xffffffffu, inc, 31);
    inc -= s;
#pragma unroll
    for (int q = 0; q < 3; q++) {
        const int n = lane * 3 + q;
        reinterpret_cast<int*>(smem + SM_NST)[n] = inc * 4;
        reinterpret_cast<int*>(smem + SM_NSTEP)[n] = n < NPB ? st[q] : (1 << 28);
        reinterpret_cast<int*>(smem + SM_DEG)[n] += c[q] >> 1;
        if (c[q] < st[q] * 4) put_rec(smem, (inc + st[q]) * 4 - 2, NULLREC);
        if (c[q] == 0) put_rec(smem, inc * 4, NULLREC);
        inc += st[q];
    }
    if (lane < 24) put_rec(smem, total * 4 + lane * 2, NULLREC);
}

template <bool SLOW>
__device__ __forceinline__ void run_round(unsigned char* smem, const char* __restrict__ ptab, uint32_t half_hi,
                                          const __nv_bfloat16* __restrict__ w2, __nv_bfloat16* __restrict__ out, bool first_round, bool last_round) {
    const uint32_t sb = (uint32_t)__cvta_generic_to_shared(smem);
    const int lane = threadIdx.x & 31, warp = __shfl_sync(0xffffffffu, threadIdx.x >> 5, 0);
    const int hf = lane >> 4, cl = lane & 15;
    const int* nst = reinterpret_cast<const int*>(smem + SM_NST);
    const int n0 = nst[lane * 3], n1 = nst[lane * 3 + 1], n2 = nst[lane * 3 + 2];
    const int total4 = __reduce_max_sync(0xffffffffu, n2);
    const int groups = (total4 + 12) >> 4;
    const int base = groups / NWARPS, ex = groups % NWARPS;
    int left = base + (warp < ex ? 1 : 0);
    {
        const int o0 = (warp * base + min(warp, ex)) * 16, o1 = o0 + left * 16;
        const uint4* lp = reinterpret_cast<const uint4*>(smem + SM_LIST + hf * (CAPS * 4) + o0);
        const char* pb = ptab + cl * 16;
        int node = __reduce_add_sync(0xffffffffu, (n0 <= o0) + (n1 <= o0) + (n2 <= o0)) - 1;
        int rem = (__reduce_min_sync(0xffffffffu, n0 > o0 ? n0 : n1 > o0 ? n1 : n2 > o0 ? n2 : total4) - o0) >> 2;
        bool head_split = !__any_sync(0xffffffffu, n0 == o0 || n1 == o0 || n2 == o0);
        const bool tail_split = o1 < total4 && !__any_sync(0xffffffffu, n0 == o1 || n1 == o1 || n2 == o1);
        uint32_t we[4], q[4];
#pragma unroll
        for (int i = 0; i < 4; i++) we[i] = half_bf16x2(reinterpret_cast<const uint32_t*>(smem + SM_WE)[(cl >> 2) * 16 + i * 4 + (cl & 3)]);
        float acc[8];
        uint32_t qa = sb + SM_Q + node * 320 + cl * 16;
        auto next_node = [&]() {
            asm volatile("ld.shared.v4.u32 {%0,%1,%2,%3}, [%4];" : "=r"(q[0]), "=r"(q[1]), "=r"(q[2]), "=r"(q[3]) : "r"(qa));
            qa += 320;
#pragma unroll
            for (int i = 0; i < 8; i++) acc[i] = 0.f;
        };
        auto store_node = [&](bool add_carry) {
            float o[4];
#pragma unroll
            for (int i = 0; i < 4; i++)
                o[i] = (hf ? acc[4 + i] : acc[i]) + __shfl_xor_sync(0xffffffffu, hf ? acc[i] : acc[4 + i], 16);
            if (add_carry) {
                int f = 0;
                for (int spin = 0; !f && spin < SPIN_MAX; spin++)
                    asm volatile("ld.acquire.cta.shared.u32 %0, [%1];" : "=r"(f) : "r"(sb + SM_FLAG + warp * 4 + 4) : "memory");
                const float4 c = *reinterpret_cast<const float4*>(smem + SM_CARRY + (threadIdx.x + 32) * 16);
                o[0] += c.x; o[1] += c.y; o[2] += c.z; o[3] += c.w;
            }
            if (head_split) {
                *reinterpret_cast<float4*>(smem + SM_CARRY + threadIdx.x * 16) = make_float4(o[0], o[1], o[2], o[3]);
                __syncwarp();
                asm volatile("st.release.cta.shared.u32 [%0], 1;" :: "r"(sb + SM_FLAG + warp * 4) : "memory");
                head_split = false;
            } else {
                asm volatile("st.shared.v2.u32 [%0], {%1,%2};" :: "r"(sb + SM_AGG + (cl >> 3) * (96 * 128) + hf * 8 + node * 128 + (((cl ^ node) & 7) << 4)),
                             "r"(pack_bf16(o[0], o[1])), "r"(pack_bf16(o[2], o[3])) : "memory");
            }
        };
        auto step = [&](uint4& p, uint32_t rec, uint32_t nxt, int d) {
            const uint32_t pv[4] = {p.x, p.y, p.z, p.w};
            uint32_t z[4];
#pragma unroll
            for (int i = 0; i < 4; i++) z[i] = fma_hi(half_hi, pv[i], fma_hi(rec, we[i], q[i]));
            p = ld_gather(pb, nxt);
#pragma unroll
            for (int i = 0; i < 4; i++) {
                acc[2 * i]     += silu_from_half(__uint_as_float(prmt(z[i], 0, 0x1044)));
                acc[2 * i + 1] += silu_from_half(bf_hi(z[i]));
            }
            if (__builtin_expect(rem == d + 1, 0)) {
                store_node(false);
                node++;
                int ns;
                asm volatile("ld.shared.u32 %0, [%1];" : "=r"(ns) : "r"(sb + SM_NSTEP + node * 4));
                rem += __reduce_max_sync(0xffffffffu, ns);
                next_node();
            }
        };
        next_node();
        __syncthreads();
        TS(5);
        uint4 ra = lp[0];
        uint4 p0 = ld_gather(pb, ra.x), p1 = ld_gather(pb, ra.y);
        if (first_round) {
            const int tid = threadIdx.x;
            const int h = tid >> 3, p = (h & 0x61) | ((h & 6) << 2) | ((h >> 2) & 6);
#pragma unroll
            for (int j = 0; j < 4; j++)
                asm volatile("cp.async.ca.shared.global [%0], [%1], 4;" :: "r"(sb + SM_W2 + p * 128 + (((((tid & 4) | j) ^ p) & 7) << 4) + (tid & 3) * 4),
                             "l"(w2 + tid * 8 + j * 2) : "memory");
            asm volatile("cp.async.commit_group;" ::: "memory");
        }
        while (left > 0) {
            const uint4 rb = lp[1];
            step(p0, ra.x, ra.z, 0); step(p1, ra.y, ra.w, 1); step(p0, ra.z, rb.x, 2); step(p1, ra.w, rb.y, 3);
            if (left == 1) break;
            ra = lp[2];
            step(p0, rb.x, rb.z, 4); step(p1, rb.y, rb.w, 5); step(p0, rb.z, ra.x, 6); step(p1, rb.w, ra.y, 7);
            lp += 2; rem -= 8; left -= 2;
        }
        if (tail_split) store_node(true);
    }
    const int rows = min(NPB, N_NODES - (int)blockIdx.x * NPB);
    const int* deg = reinterpret_cast<const int*>(smem + SM_DEG);
    const int r0 = warp * 16 + (lane >> 2), t = lane & 3;
    float d[32];
    if (!SLOW && warp < 8) {
        const float dg0 = (float)deg[min(r0, NPB)], dg1 = (float)deg[min(r0 + 8, NPB)];
#pragma unroll
        for (int J = 0; J < 2; J++) {
            const uint4 b = *reinterpret_cast<const uint4*>(smem + SM_B2 + J * 64 + t * 16);
            const uint32_t bv[4] = {b.x, b.y, b.z, b.w};
#pragma unroll
            for (int j = 0; j < 4; j++) {
                float* c = d + 16 * J + 4 * j;
                c[0] = dg0 * bf_lo(bv[j]); c[1] = dg0 * bf_hi(bv[j]); c[2] = dg1 * bf_lo(bv[j]); c[3] = dg1 * bf_hi(bv[j]);
            }
        }
#pragma unroll
        for (int i = 0; i < 32; i++) asm volatile("" : "+f"(d[i]) :: "memory");
    }
    asm volatile("cp.async.wait_group 0;" ::: "memory");
    fence_async();
    __syncthreads();
    TS(6);
    if (SLOW) {
        const int row = threadIdx.x >> 3, ch = threadIdx.x & 7;
        if (row < rows) {
            float v[8];
            float* acc = g_outacc + (blockIdx.x * NPB + row) * 64 + ch * 8;
#pragma unroll
            for (int i = 0; i < 8; i++) v[i] = first_round ? 0.f : acc[i];
            for (int k = 0; k < 128; k++) {
                const float a = bf_lo(*reinterpret_cast<const unsigned short*>(smem + SM_AGG + (k >> 6) * (96 * 128) + row * 128 + ((((k >> 3) ^ row) & 7) << 4) + (k & 7) * 2));
                const uint4 w = *reinterpret_cast<const uint4*>(smem + SM_W2 + k * 128 + (((ch ^ k) & 7) << 4));
                const uint32_t wv[4] = {w.x, w.y, w.z, w.w};
#pragma unroll
                for (int i = 0; i < 4; i++) { v[2 * i] = fmaf(a, bf_lo(wv[i]), v[2 * i]); v[2 * i + 1] = fmaf(a, bf_hi(wv[i]), v[2 * i + 1]); }
            }
#pragma unroll
            for (int q = 0; q < 4; q++) {
                const int col2 = (ch >> 2) * 16 + q * 4 + (ch & 3);
                const uint32_t bv = reinterpret_cast<const uint32_t*>(smem + SM_B2)[col2];
                if (last_round)
                    reinterpret_cast<uint32_t*>(out)[(blockIdx.x * NPB + row) * 32 + col2] =
                        pack_bf16(fmaf((float)deg[row], bf_lo(bv), v[2 * q]), fmaf((float)deg[row], bf_hi(bv), v[2 * q + 1]));
                else { acc[2 * q] = v[2 * q]; acc[2 * q + 1] = v[2 * q + 1]; }
            }
        }
    } else if (warp < 8) {
        const uint64_t da = desc_sw128(sb + SM_AGG + (warp >> 2) * 8192), db = desc_sw128(sb + SM_W2);
        wgmma_begin(d);
#pragma unroll
        for (int s = 0; s < 8; s++) wgmma_ss(d, da + (s >> 2) * (96 * 8) + (s & 3) * 2, db + s * 128, 1);
        wgmma_end(d);
        uint4* o = reinterpret_cast<uint4*>(out) + (blockIdx.x * NPB + r0) * 8 + t;
#pragma unroll
        for (int u = 0; u < 2; u++) {
#pragma unroll
            for (int J = 0; J < 2; J++) {
                const float* c = d + 16 * J + 2 * u;
                if (r0 + 8 * u < rows)
                    o[u * 64 + J * 4] = make_uint4(pack_bf16(c[0], c[1]), pack_bf16(c[4], c[5]), pack_bf16(c[8], c[9]), pack_bf16(c[12], c[13]));
            }
        }
    }
    TS(7);
}

__device__ __noinline__ void run_slow(unsigned char* smem, const char* ptab, uint32_t half_hi, const __nv_bfloat16* w2, __nv_bfloat16* out, uint32_t tag) {
    const int tid = threadIdx.x, lane = tid & 31, warp = tid >> 5;
    int* cur = reinterpret_cast<int*>(smem + SM_HIST);
    int* cnt = reinterpret_cast<int*>(smem + SM_CNT);
    const int* nst = reinterpret_cast<const int*>(smem + SM_NST);
    const uint32_t* seg = reinterpret_cast<const uint32_t*>(smem + SM_SEG);
    for (int c0 = 0; c0 < GRID;) {
        __syncthreads();
        if (tid < 160 + 96) cur[tid] = 0;
        if (tid < 32) reinterpret_cast<int*>(smem + SM_FLAG)[tid] = 0;
        int c1 = c0;
        for (int sum = 0; c1 < GRID; c1++) {
            sum += (int)(seg[c1] >> 16) - (int)(seg[c1] & 0xFFFF);
            if (sum > CAPN) break;
        }
        __syncthreads();
        for (int pass = 0; pass < 2; pass++) {
            for (int c = c0; c < c1; c++) {
                const int s = seg[c] & 0xFFFF, e = seg[c] >> 16;
                const bool wide = e - s > 256;
                if (!wide && (c & (NWARPS - 1)) != warp) continue;
                for (int i = s + (wide ? tid : lane); i < e; i += (wide ? THREADS : 32)) {
                    const uint32_t* p = reinterpret_cast<const uint32_t*>(g_rec + c * (CHUNK * 5 / 16));
                    uint32_t r, d;
                    int spin = 0;
                    do {
                        r = ld_relaxed(p + i);
                        d = ld_relaxed(p + CHUNK + (i >> 2)) ^ tag_dst(tag);
                    } while ((((r ^ tag_rec(tag)) & 0xC000u) | (d & 0x80808080u)) != 0 && ++spin < SPIN_MAX);
                    const uint32_t l = min((d >> ((i & 3) * 8)) & 0xFFu, NPB - 1u);
                    if (pass == 0) atomicAdd(&cnt[l], 2);
                    else put_rec(smem, nst[l] + atomicAdd(&cur[l], 2), r);
                }
            }
            __syncthreads();
            if (pass == 0) {
                if (warp == 0) scan_nodes(smem, lane);
                __syncthreads();
            }
        }
        run_round<true>(smem, ptab, half_hi, w2, out, c0 == 0, c1 >= GRID);
        c0 = c1;
    }
}

template <int PHASES>
__global__ void __launch_bounds__(THREADS, 1)
mpnn_kernel(const __nv_bfloat16* __restrict__ x, const unsigned short* __restrict__ e_attr,
            const int* __restrict__ src, const int* __restrict__ dst,
            const __nv_bfloat16* __restrict__ w1, const void* __restrict__ b1,
            const __nv_bfloat16* __restrict__ w2, const void* __restrict__ b2,
            __nv_bfloat16* __restrict__ out, const char* __restrict__ ptab, uint32_t half_hi) {
    if (PHASES == 4) { if (threadIdx.x == 0) g_epoch[0] = g_epoch[0] + 1; return; }
    extern __shared__ __align__(1024) unsigned char smem[];
    const uint32_t sb = (uint32_t)__cvta_generic_to_shared(smem);
    const int tid = threadIdx.x, lane = tid & 31;
    const int warp = __shfl_sync(0xffffffffu, tid >> 5, 0);
    const int cta = blockIdx.x;
    int* hist = reinterpret_cast<int*>(smem + SM_HIST);
    TS(0);

    if ((PHASES & 1) && tid == THREADS - 1) {
        asm volatile("mbarrier.init.shared::cta.b64 [%0], 1;" :: "r"(sb + SM_MBAR) : "memory");
        asm volatile("fence.mbarrier_init.release.cluster;" ::: "memory");
    }
    uint2 vd[EIT];
    const int e0 = cta * CHUNK + tid * 2;
    const bool tail_ok = tid * 2 + (EIT - 1) * THREADS * 2 < CHUNK && e0 + (EIT - 1) * THREADS * 2 < N_EDGES;
    auto my_tab = [&]() { return &g_tab[((threadIdx.x >> 1) * GRID + blockIdx.x) * 2 + (threadIdx.x & 1)]; };
    if (PHASES & 1) {
        vd[EIT - 1] = make_uint2(0, 0);
#pragma unroll
        for (int j = 0; j < EIT; j++) if (j < EIT - 1 || tail_ok) vd[j] = ld_stream2(dst + e0 + j * THREADS * 2);
    }
    if (tid < 160 + 96 + 96 + 32) hist[tid] = tid == 140 ? 44151 : 0;
    uint32_t vb1 = 0;
    if (warp >= 26 && warp <= 28) vb1 = ld_stream1(warp == 28 ? g_epoch : reinterpret_cast<const uint32_t*>(b1) + (tid & 63));
    if (PHASES & 1) {
        __syncthreads();
        if (tid == THREADS - 1) {
            const int n = min(CHUNK, N_EDGES - cta * CHUNK);
            asm volatile("mbarrier.arrive.expect_tx.shared::cta.b64 _, [%0], %1;" :: "r"(sb + SM_MBAR), "r"(n * 6) : "memory");
            asm volatile("cp.async.bulk.shared::cluster.global.mbarrier::complete_tx::bytes [%0], [%1], %2, [%3];"
                         :: "r"(sb + SM_SRC), "l"(src + cta * CHUNK), "r"(n * 4), "r"(sb + SM_MBAR) : "memory");
            asm volatile("cp.async.bulk.shared::cluster.global.mbarrier::complete_tx::bytes [%0], [%1], %2, [%3];"
                         :: "r"(sb + SM_E), "l"(e_attr + cta * CHUNK), "r"(n * 2), "r"(sb + SM_MBAR) : "memory");
        }
    }
    if (PHASES == 3 && tid < GRID * 2) st_relaxed(my_tab(), make_uint4(0, 0, 0, 0));
    auto owner = [](uint32_t v) { return ((v & 16383u) * 44151u) >> 22; };
    if (PHASES & 1) {
        const uint32_t mul = hist[140];
#pragma unroll
        for (int j = 0; j < EIT; j++) {
            if (j < EIT - 1 || tail_ok) {
                const uint32_t r0 = atomicAdd(&hist[(vd[j].x * mul) >> 22], 1 << 14), r1 = atomicAdd(&hist[(vd[j].y * mul) >> 22], 1 << 14);
                vd[j].x |= r0; vd[j].y |= r1;
            }
        }
    }
    {
        const uint32_t dw = sb + SM_W1 + ((tid >> 3) & 1) * 8192 + (tid >> 4) * 128 + (((tid ^ (tid >> 4)) & 7) << 4);
        if (tid < 96 * 8) cp16(sb + SM_X + (tid >> 3) * 128 + (((tid ^ (tid >> 3)) & 7) << 4), x + min(cta * (NPB * 64) + tid * 8, N_NODES * 64 - 8));
        else if (tid < 96 * 8 + 24) {
            const int i = tid - 96 * 8;
            cp16(sb + SM_WE + i * 16, (i < 16 ? reinterpret_cast<const char*>(w1 + 128 * 128) : reinterpret_cast<const char*>(b2) - 256) + i * 16);
        }
        cp16(dw, w1 + tid * 8);
        cp16(dw + 16384, w1 + tid * 8 + 64 * 128);
        asm volatile("cp.async.commit_group;" ::: "memory");
    }
    if (warp >> 1 == 13)
        *reinterpret_cast<float2*>(smem + SM_B1 + (warp & 1) * 256 + (lane & 3) * 64 + (lane >> 2) * 8) = make_float2(0.5f * bf_lo(vb1), 0.5f * bf_hi(vb1));
    if (warp == 28) *reinterpret_cast<unsigned*>(smem + SM_EPOCH) = vb1;
    __syncthreads();
    TS(2);
    if ((PHASES & 1) && warp == NWARPS - 1) {
        int h[5], s = 0;
#pragma unroll
        for (int q = 0; q < 5; q++) { h[q] = hist[lane * 5 + q]; s += h[q]; }
        int inc = s;
#pragma unroll
        for (int o = 1; o < 32; o <<= 1) {
            const int v = __shfl_up_sync(0xffffffffu, inc, o);
            if (lane >= o) inc += v;
        }
        inc -= s;
#pragma unroll
        for (int q = 0; q < 5; q++) { hist[lane * 5 + q] = inc; inc += h[q]; }
    }

    const unsigned epoch = *reinterpret_cast<const unsigned*>(smem + SM_EPOCH);
    const uint32_t tag = ((epoch & 0xFFFFu) + 1u) << 14;

    if (PHASES & 1) {
        __syncthreads();
        TS(9);
        unsigned char* stage = smem + SM_STAGE;
#pragma unroll
        for (int j = 0; j < EIT; j++) {
            const uint32_t o0 = owner(vd[j].x), o1 = owner(vd[j].y);
            vd[j].x += hist[o0] - o0 * NPB + (tag_dst(tag) & 0x80u);
            vd[j].y += hist[o1] - o1 * NPB + (tag_dst(tag) & 0x80u);
        }
        uint32_t ok = 0;
        for (int spin = 0; !ok && spin < SPIN_MAX; spin++)
            asm volatile("{.reg .pred p; mbarrier.try_wait.parity.shared::cta.b64 p, [%1], 0; selp.u32 %0, 1, 0, p;}"
                         : "=r"(ok) : "r"(sb + SM_MBAR) : "memory");
#pragma unroll
        for (int j = 0; j < EIT; j++) {
            if (j < EIT - 1 || tail_ok) {
                const uint2 vs = *reinterpret_cast<const uint2*>(smem + SM_SRC + (j * THREADS + tid) * 8);
                const uint32_t ve = *reinterpret_cast<const uint32_t*>(smem + SM_E + (j * THREADS + tid) * 4);
                *reinterpret_cast<uint32_t*>(stage + (vd[j].x >> 12)) = prmt(vs.x | tag_rec(tag), ve, 0x5410);
                *reinterpret_cast<uint32_t*>(stage + (vd[j].y >> 12)) = prmt(vs.y | tag_rec(tag), ve, 0x7610);
                stage[CHUNK * 4 + (vd[j].x >> 14)] = (unsigned char)vd[j].x;
                stage[CHUNK * 4 + (vd[j].y >> 14)] = (unsigned char)vd[j].y;
            }
        }
    }
    asm volatile("cp.async.wait_group 0;" ::: "memory");
    fence_async();
    __syncthreads();
    TS(10);
    if (PHASES & 1) {
        const unsigned char* stage = smem + SM_STAGE;
#pragma unroll
        for (int j = 0; j < 2; j++)
            if (j == 0 || THREADS + tid < CHUNK * 5 / 16)
                st_relaxed(g_rec + cta * (CHUNK * 5 / 16) + j * THREADS + tid, *reinterpret_cast<const uint4*>(stage + (j * THREADS + tid) * 16));
        __syncthreads();
        if (tid < GRID * 2) {
            const uint32_t se = (hist[tid >> 1] >> 14) | (hist[(tid >> 1) + 1] << 2);
            st_relaxed(my_tab(), make_uint4(se, tag, se, tag));
        }
        TS(3);
    }

    {
        const int nq = warp >> 3, g = lane >> 2, t = lane & 3;
        const int r0 = (warp & 7) * 16 + g;
        float d[32];
        const uint64_t da = desc_sw128(sb + SM_X + ((warp >> 2) & 1) * 8192), db = desc_sw128(sb + SM_W1 + nq * 8192);
        asm volatile("wgmma.fence.sync.aligned;" ::: "memory");
#pragma unroll
        for (int s = 0; s < 4; s++) wgmma_ss(d, da + s * 2, db + s * 128, s);
        wgmma_end(d);
        if ((warp & 7) < 6) {
            if (nq >= 2) {
#pragma unroll
                for (int j = 0; j < 4; j++) {
                    const float4 b = *reinterpret_cast<const float4*>(smem + SM_B1 + (nq & 1) * 256 + t * 64 + j * 16);
                    float* c = d + 8 * j;
                    c[0] = fmaf(c[0], 0.5f, b.x); c[1] = fmaf(c[1], 0.5f, b.y); c[2] = fmaf(c[2], 0.5f, b.x); c[3] = fmaf(c[3], 0.5f, b.y);
                    c[4] = fmaf(c[4], 0.5f, b.z); c[5] = fmaf(c[5], 0.5f, b.w); c[6] = fmaf(c[6], 0.5f, b.z); c[7] = fmaf(c[7], 0.5f, b.w);
                }
            }
            const int pitch = nq >= 2 ? 320 : 256;
            unsigned char* o = smem + (nq >= 2 ? SM_Q : SM_SRC) + r0 * pitch + (nq & 1) * 128 + t * 16;
#pragma unroll
            for (int u = 0; u < 2; u++) {
#pragma unroll
                for (int J = 0; J < 2; J++) {
                    const float* c = d + 16 * J + 2 * u;
                    *reinterpret_cast<uint4*>(o + u * 8 * pitch + J * 64) =
                        make_uint4(pack_bf16(c[0], c[1]), pack_bf16(c[4], c[5]), pack_bf16(c[8], c[9]), pack_bf16(c[12], c[13]));
                }
            }
        }
        if ((PHASES & 1) && cta == 0 && tid < 16) g_P[N_NODES * 16 + tid] = make_uint4(0xF149F149u, 0xF149F149u, 0xF149F149u, 0xF149F149u);
    }
    if (PHASES & 1) {
        if (warp < 16) { fence_async(); asm volatile("bar.arrive 1, 544;" ::: "memory"); }
        if (warp == NWARPS - 1) {
            asm volatile("bar.sync 1, 544;" ::: "memory");
            if (lane == 0) {
                asm volatile("cp.async.bulk.global.shared::cta.bulk_group [%0], [%1], %2;"
                             :: "l"(g_P + cta * NPB * 16), "r"(sb + SM_SRC), "r"(min(NPB, N_NODES - cta * NPB) * 256) : "memory");
                asm volatile("cp.async.bulk.commit_group;" ::: "memory");
                asm volatile("cp.async.bulk.wait_group 0;" ::: "memory");
                asm volatile("fence.proxy.async.global;" ::: "memory");
                if (PHASES == 3) asm volatile("red.release.gpu.global.add.u32 [%0], 1;" :: "l"(&g_pcnt) : "memory");
            }
        }
    }
    TS(1);
    if (!(PHASES & 2)) return;

    const int c = tid / LPC, j = tid - c * LPC;
    int s = 0, e = 0;
    if (c < GRID) {
        const uint2* tp = reinterpret_cast<const uint2*>(&g_tab[(cta * GRID + c) * 2]);
        uint2 v = ld_relaxed(tp);
        for (int spin = 0; v.y != tag && spin < SPIN_MAX; spin++) v = ld_relaxed(tp);
        if (v.y != tag) v.x = 0;
        s = v.x & 0xFFFF; e = v.x >> 16;
        reinterpret_cast<uint32_t*>(smem + SM_SEG)[c] = v.x;
    }
    TS(11);
    const int nquad = ((e + 3) >> 2) - (s >> 2) - j;
    const uint4* rp = g_rec + c * (CHUNK * 5 / 16) + (s >> 2) + j;
    const uint32_t* dp = reinterpret_cast<const uint32_t*>(g_rec + c * (CHUNK * 5 / 16)) + CHUNK + (s >> 2) + j;
    const int kmax = __reduce_max_sync(0xffffffffu, nquad);
    uint4 r[RIT];
    uint32_t dl[RIT], y[RIT * 4], rk[RIT * 4];
    for (int spin = 0; spin < SPIN_MAX; spin++) {
        const uint32_t t = tag_rec(tag);
        uint32_t bad = 0, badd = 0;
#pragma unroll
        for (int k = 0; k < RIT; k++) {
            r[k] = make_uint4(t, t, t, t); dl[k] = tag_dst(tag);
            if (k * LPC < nquad) { r[k] = ld_relaxed(rp + k * LPC); dl[k] = ld_relaxed(dp + k * LPC); }
        }
#pragma unroll
        for (int k = 0; k < RIT; k++) {
            bad |= (r[k].x ^ t) | (r[k].y ^ t) | (r[k].z ^ t) | (r[k].w ^ t);
            dl[k] ^= tag_dst(tag);
            badd |= dl[k];
        }
        if (((bad & 0xC000u) | (badd & 0x80808080u)) == 0) break;
    }
    TS(12);
#pragma unroll
    for (int k = 0; k < RIT; k++) {
        if (k < RIT - 1 || k * LPC < kmax) {
#pragma unroll
            for (int i = 0; i < 4; i++) {
                const bool mine = (uint32_t)(j * 4 - (s & 3) + k * LPC * 4 + i) < (uint32_t)(e - s);
                y[4 * k + i] = prmt(dl[k], NPB, mine ? 0x7770 + i : 0x7774) * 4;
                asm volatile("{.reg .pred p; setp.lt.u32 p, %1, %3; @p atom.shared.add.u32 %0, [%2], 2;}"
                             : "=r"(rk[4 * k + i]) : "r"(y[4 * k + i]), "r"(sb + SM_CNT + y[4 * k + i]), "n"(4 * NPB) : "memory");
            }
        }
    }
    auto acquire_p = [&]() {
        if (PHASES == 3 && tid == THREADS - 32) {
            const unsigned target = (epoch + 1u) * GRID;
            unsigned v;
            int spin = 0;
            do {
                asm volatile("ld.acquire.gpu.global.u32 %0, [%1];" : "=r"(v) : "l"(&g_pcnt) : "memory");
            } while ((int)(v - target) < 0 && ++spin < SPIN_MAX);
            if (cta == 0) g_epoch[0] = epoch + 1u;
        }
    };
    if (warp != NWARPS - 1) {
        uint32_t slow;
        asm volatile("{.reg .pred p, q; setp.gt.s32 p, %1, %2; bar.red.or.pred q, 2, %3, p; selp.u32 %0, 1, 0, q;}"
                     : "=r"(slow) : "r"(nquad + j), "n"(LPC * RIT), "n"(THREADS - 32) : "memory");
        TS(4);
        if (warp == 0) {
            if (!slow) scan_nodes(smem, lane);
            *reinterpret_cast<uint32_t*>(smem + SM_EPOCH + 4) = slow;
        }
    }
    __syncthreads();
    acquire_p();
    if (*reinterpret_cast<const uint32_t*>(smem + SM_EPOCH + 4)) {
        run_slow(smem, ptab, half_hi, w2, out, tag);
        return;
    }
#pragma unroll
    for (int k = 0; k < RIT; k++) {
        if (k < RIT - 1 || k * LPC < kmax) {
            const uint32_t rv[4] = {r[k].x, r[k].y, r[k].z, r[k].w};
#pragma unroll
            for (int i = 0; i < 4; i++) rk[4 * k + i] += *reinterpret_cast<const int*>(smem + SM_NST + y[4 * k + i]);
#pragma unroll
            for (int i = 0; i < 4; i++) if (y[4 * k + i] < 4 * NPB) put_rec(smem, rk[4 * k + i], rv[i]);
        }
    }
    run_round<false>(smem, ptab, half_hi, w2, out, true, true);
}

}

extern "C" void kernel_launch(void* const* d_in, const int* in_sizes, int n_in, void* d_out, int out_size) {
    (void)in_sizes; (void)n_in; (void)out_size;
    const __nv_bfloat16* x  = (const __nv_bfloat16*)d_in[0];
    const unsigned short* e = (const unsigned short*)d_in[1];
    const int* src          = (const int*)d_in[2];
    const int* dst          = (const int*)d_in[3];
    const __nv_bfloat16* w1 = (const __nv_bfloat16*)d_in[4];
    const void* b1          = d_in[5];
    const __nv_bfloat16* w2 = (const __nv_bfloat16*)d_in[6];
    const void* b2          = d_in[7];
    __nv_bfloat16* out = (__nv_bfloat16*)d_out;

    static int fused = -1;
    static void* ptab = nullptr;
    if (fused < 0) {
        cudaFuncSetAttribute(mpnn_kernel<3>, cudaFuncAttributeMaxDynamicSharedMemorySize, SM_TOTAL);
        cudaFuncSetAttribute(mpnn_kernel<1>, cudaFuncAttributeMaxDynamicSharedMemorySize, SM_TOTAL);
        cudaFuncSetAttribute(mpnn_kernel<2>, cudaFuncAttributeMaxDynamicSharedMemorySize, SM_TOTAL);
        cudaGetSymbolAddress(&ptab, g_P);
        int dev = 0, sms = 0, per_sm = 0;
        cudaGetDevice(&dev);
        cudaDeviceGetAttribute(&sms, cudaDevAttrMultiProcessorCount, dev);
        cudaOccupancyMaxActiveBlocksPerMultiprocessor(&per_sm, mpnn_kernel<3>, THREADS, SM_TOTAL);
        fused = (sms * per_sm >= GRID) ? 1 : 0;
    }
    const char* pt = (const char*)ptab;
    if (fused) {
        mpnn_kernel<3><<<GRID, THREADS, SM_TOTAL>>>(x, e, src, dst, w1, b1, w2, b2, out, pt, 0x3F000000u);
    } else {
        mpnn_kernel<1><<<GRID, THREADS, SM_TOTAL>>>(x, e, src, dst, w1, b1, w2, b2, out, pt, 0x3F000000u);
        mpnn_kernel<2><<<GRID, THREADS, SM_TOTAL>>>(x, e, src, dst, w1, b1, w2, b2, out, pt, 0x3F000000u);
        mpnn_kernel<4><<<1, 32>>>(x, e, src, dst, w1, b1, w2, b2, out, pt, 0x3F000000u);
    }
}
```

```cpp
#include <cuda_runtime.h>
#include <cuda_bf16.h>
#include <stdint.h>

namespace {

constexpr int N_NODES = 12500;
constexpr int N_EDGES = 800000;
constexpr int GRID    = 132;
constexpr int THREADS = 1024;
constexpr int NWARPS  = THREADS / 32;
constexpr int NPB     = 95;
constexpr int CHUNK   = 6064;
constexpr int EIT     = 3;
constexpr int LPC     = 7;
constexpr int RIT     = 3;
constexpr int CAPN    = GRID * LPC * RIT * 4;
constexpr int CAPS    = CAPN / 2 + NPB + 13;
constexpr uint32_t NULLREC = N_NODES;
constexpr int SPIN_MAX = 1 << 22;
static_assert(GRID * CHUNK >= N_EDGES && (GRID - 1) * CHUNK < N_EDGES && CHUNK % 16 == 0 && N_EDGES % 8 == 0 && CHUNK * 5 <= THREADS * 32, "chunking");
static_assert(EIT * THREADS * 2 >= CHUNK && GRID * LPC <= THREADS - 32 && GRID * NPB >= N_NODES, "coverage");
static_assert(N_EDGES - (GRID - 1) * CHUNK >= (EIT - 1) * THREADS * 2, "only the last load is predicated");
static_assert(CAPN >= CHUNK && CAPS % 8 == 4, "list capacity");

constexpr int SM_X     = 0;
constexpr int SM_W1    = SM_X + 96 * 128;
constexpr int SM_W2    = SM_W1 + 4 * 8192;
constexpr int SM_AGG   = SM_W2 + 128 * 128;
constexpr int SM_CARRY = SM_AGG + 2 * 96 * 128;
constexpr int SM_STAGE = SM_AGG;
constexpr int SM_Q     = SM_CARRY + 32 * 512;
constexpr int SM_LIST  = SM_Q + 96 * 320;
constexpr int SM_HIST  = SM_LIST + CAPS * 8;
constexpr int SM_CNT   = SM_HIST + 160 * 4;
constexpr int SM_DEG   = SM_CNT + 96 * 4;
constexpr int SM_FLAG  = SM_DEG + 96 * 4;
constexpr int SM_NST   = SM_FLAG + 32 * 4;
constexpr int SM_NSTEP = SM_NST + 96 * 4;
constexpr int SM_SEG   = SM_NSTEP + 96 * 4;
constexpr int SM_WE    = SM_SEG + GRID * 4;
constexpr int SM_B2    = SM_WE + 256;
constexpr int SM_B1    = SM_B2 + 128;
constexpr int SM_EPOCH = SM_B1 + 512;
constexpr int SM_MBAR  = SM_EPOCH + 8;
constexpr int SM_SRC   = SM_MBAR + 8;
constexpr int SM_E     = SM_SRC + CHUNK * 4;
constexpr int SM_TOTAL = SM_E + CHUNK * 2;
static_assert(SM_STAGE + CHUNK * 5 <= SM_Q && SM_TOTAL <= 232448, "smem");
static_assert(SM_W1 % 1024 == 0 && SM_AGG % 1024 == 0 && SM_Q % 128 == 0 && SM_LIST % 16 == 0 && CHUNK * 6 >= 96 * 256 && SM_WE % 16 == 0 && SM_SRC % 16 == 0, "alignment");

__device__ uint4    g_P[(N_NODES + 1) * 16];
__device__ uint4    g_rec[GRID * (CHUNK * 5 / 16)];
__device__ uint4    g_tab[GRID * GRID * 2];
__device__ float    g_outacc[N_NODES * 64];
__device__ unsigned g_epoch[1];
__device__ unsigned g_pcnt;
#define TS(i)

__device__ __forceinline__ void cp16(uint32_t dst, const void* src) {
    asm volatile("cp.async.cg.shared.global [%0], [%1], 16;" :: "r"(dst), "l"(src) : "memory");
}
__device__ __forceinline__ uint2 ld_stream2(const void* p) {
    uint2 v;
    asm volatile("ld.global.L1::no_allocate.v2.u32 {%0,%1}, [%2];" : "=r"(v.x), "=r"(v.y) : "l"(p) : "memory");
    return v;
}
__device__ __forceinline__ uint32_t ld_stream1(const void* p) {
    uint32_t v;
    asm volatile("ld.global.L1::no_allocate.u32 %0, [%1];" : "=r"(v) : "l"(p) : "memory");
    return v;
}
__device__ __forceinline__ uint4 ld_relaxed(const uint4* p) {
    unsigned long long a, b;
    asm volatile("ld.relaxed.gpu.global.v2.u64 {%0,%1}, [%2];" : "=l"(a), "=l"(b) : "l"(p) : "memory");
    return make_uint4((uint32_t)a, (uint32_t)(a >> 32), (uint32_t)b, (uint32_t)(b >> 32));
}
__device__ __forceinline__ uint2 ld_relaxed(const uint2* p) {
    unsigned long long a;
    asm volatile("ld.relaxed.gpu.global.u64 %0, [%1];" : "=l"(a) : "l"(p) : "memory");
    return make_uint2((uint32_t)a, (uint32_t)(a >> 32));
}
__device__ __forceinline__ uint32_t ld_relaxed(const uint32_t* p) {
    uint32_t a;
    asm volatile("ld.relaxed.gpu.global.u32 %0, [%1];" : "=r"(a) : "l"(p) : "memory");
    return a;
}
__device__ __forceinline__ uint32_t tag_rec(uint32_t tag) { return (tag & 0x4000u) ? 0x4000u : 0x8000u; }
__device__ __forceinline__ uint32_t tag_dst(uint32_t tag) { return (tag & 0x4000u) ? 0x80808080u : 0u; }
__device__ __forceinline__ void st_relaxed(uint4* p, uint4 v) {
    const unsigned long long a = v.x | ((unsigned long long)v.y << 32), b = v.z | ((unsigned long long)v.w << 32);
    asm volatile("st.relaxed.gpu.global.v2.u64 [%0], {%1,%2};" :: "l"(p), "l"(a), "l"(b) : "memory");
}
__device__ __forceinline__ uint4 ld_gather(const char* base, uint32_t rec) {
    uint4 v;
    asm volatile("{.reg .u64 a; .reg .u32 r; and.b32 r, %5, 0x3FFF; mad.wide.u32 a, r, 256, %4;\n"
                 "ld.global.L1::no_allocate.v4.u32 {%0,%1,%2,%3}, [a];}"
                 : "=r"(v.x), "=r"(v.y), "=r"(v.z), "=r"(v.w) : "l"(base), "r"(rec));
    return v;
}
__device__ __forceinline__ uint64_t desc_sw128(uint32_t saddr) {
    return (uint64_t)((saddr & 0x3FFFF) >> 4) | ((uint64_t)1 << 16) | ((uint64_t)64 << 32) | ((uint64_t)1 << 62);
}
__device__ __forceinline__ void wgmma_ss(float (&d)[32], uint64_t da, uint64_t db, int accumulate) {
    asm volatile("{.reg .pred p; setp.ne.b32 p, %34, 0;\n"
                 "wgmma.mma_async.sync.aligned.m64n64k16.f32.bf16.bf16 {%0,%1,%2,%3,%4,%5,%6,%7,%8,%9,%10,%11,%12,%13,%14,%15,%16,%17,%18,%19,%20,%21,%22,%23,%24,%25,%26,%27,%28,%29,%30,%31}, %32, %33, p, 1, 1, 0, 1;}"
                 : "+f"(d[0]), "+f"(d[1]), "+f"(d[2]), "+f"(d[3]), "+f"(d[4]), "+f"(d[5]), "+f"(d[6]), "+f"(d[7]), "+f"(d[8]), "+f"(d[9]), "+f"(d[10]), "+f"(d[11]), "+f"(d[12]), "+f"(d[13]), "+f"(d[14]), "+f"(d[15]), "+f"(d[16]), "+f"(d[17]), "+f"(d[18]), "+f"(d[19]), "+f"(d[20]), "+f"(d[21]), "+f"(d[22]), "+f"(d[23]), "+f"(d[24]), "+f"(d[25]), "+f"(d[26]), "+f"(d[27]), "+f"(d[28]), "+f"(d[29]), "+f"(d[30]), "+f"(d[31])
                 : "l"(da), "l"(db), "r"(accumulate));
}
template <int K> __device__ __forceinline__ void wgmma_begin(float (&d)[K]) {
#pragma unroll
    for (int i = 0; i < K; i++) asm volatile("" : "+f"(d[i]) :: "memory");
    asm volatile("wgmma.fence.sync.aligned;" ::: "memory");
}
template <int K> __device__ __forceinline__ void wgmma_end(float (&d)[K]) {
    asm volatile("wgmma.commit_group.sync.aligned;" ::: "memory");
    asm volatile("wgmma.wait_group.sync.aligned 0;" ::: "memory");
#pragma unroll
    for (int i = 0; i < K; i++) asm volatile("" : "+f"(d[i]) :: "memory");
}
__device__ __forceinline__ void fence_async() { asm volatile("fence.proxy.async.shared::cta;" ::: "memory"); }
__device__ __forceinline__ uint32_t half_bf16x2(uint32_t v) {
    uint32_t r;
    asm("mul.rn.bf16x2 %0, %1, %2;" : "=r"(r) : "r"(v), "r"(0x3F003F00u));
    return r;
}
__device__ __forceinline__ uint32_t pack_bf16(float lo, float hi) {
    uint32_t r;
    asm("cvt.rn.bf16x2.f32 %0, %1, %2;" : "=r"(r) : "f"(hi), "f"(lo));
    return r;
}
__device__ __forceinline__ float silu_from_half(float h) {
    float t;
    asm("tanh.approx.f32 %0, %1;" : "=f"(t) : "f"(h));
    return fmaf(h, t, h);
}
__device__ __forceinline__ uint32_t fma_hi(uint32_t a, uint32_t b, uint32_t c) {
    uint32_t r;
    asm("{.reg .b16 l, h; .reg .b32 t; mov.b32 {l, h}, %1; mov.b32 t, {h, h}; fma.rn.bf16x2 %0, t, %2, %3;}"
        : "=r"(r) : "r"(a), "r"(b), "r"(c));
    return r;
}
__device__ __forceinline__ uint32_t prmt(uint32_t a, uint32_t b, uint32_t s) {
    uint32_t r;
    asm("prmt.b32 %0, %1, %2, %3;" : "=r"(r) : "r"(a), "r"(b), "r"(s));
    return r;
}
__device__ __forceinline__ float bf_lo(uint32_t v) { return __uint_as_float(v << 16); }
__device__ __forceinline__ float bf_hi(uint32_t v) { return __uint_as_float(v & 0xFFFF0000u); }
__device__ __forceinline__ uint32_t list_off(uint32_t v) { return v + (v & 2u) * (CAPS * 2 - 1); }
__device__ __forceinline__ void put_rec(unsigned char* smem, uint32_t v, uint32_t rec) {
    *reinterpret_cast<uint32_t*>(smem + SM_LIST + list_off(v)) = rec;
}

__device__ __forceinline__ void scan_nodes(unsigned char* smem, int lane) {
    int* cnt = reinterpret_cast<int*>(smem + SM_CNT);
    int c[3], st[3], s = 0;
#pragma unroll
    for (int q = 0; q < 3; q++) {
        c[q] = cnt[lane * 3 + q];
        st[q] = (lane * 3 + q < NPB) ? max(1, (c[q] + 2) >> 2) : 0;
        s += st[q];
    }
    int inc = s;
#pragma unroll
    for (int o = 1; o < 32; o <<= 1) {
        const int v = __shfl_up_sync(0xffffffffu, inc, o);
        if (lane >= o) inc += v;
    }
    const int total = __shfl_sync(0xffffffffu, inc, 31);
    inc -= s;
#pragma unroll
    for (int q = 0; q < 3; q++) {
        const int n = lane * 3 + q;
        reinterpret_cast<int*>(smem + SM_NST)[n] = inc * 4;
        reinterpret_cast<int*>(smem + SM_NSTEP)[n] = n < NPB ? st[q] : (1 << 28);
        reinterpret_cast<int*>(smem + SM_DEG)[n] += c[q] >> 1;
        if (c[q] < st[q] * 4) put_rec(smem, (inc + st[q]) * 4 - 2, NULLREC);
        if (c[q] == 0) put_rec(smem, inc * 4, NULLREC);
        inc += st[q];
    }
    if (lane < 24) put_rec(smem, total * 4 + lane * 2, NULLREC);
}

template <bool SLOW>
__device__ __forceinline__ void run_round(unsigned char* smem, const char* __restrict__ ptab, uint32_t half_hi,
                                          const __nv_bfloat16* __restrict__ w2, __nv_bfloat16* __restrict__ out, bool first_round, bool last_round) {
    const uint32_t sb = (uint32_t)__cvta_generic_to_shared(smem);
    const int lane = threadIdx.x & 31, warp = __shfl_sync(0xffffffffu, threadIdx.x >> 5, 0);
    const int hf = lane >> 4, cl = lane & 15;
    const int* nst = reinterpret_cast<const int*>(smem + SM_NST);
    const int n0 = nst[lane * 3], n1 = nst[lane * 3 + 1], n2 = nst[lane * 3 + 2];
    const int total4 = __reduce_max_sync(0xffffffffu, n2);
    const int groups = (total4 + 12) >> 4;
    const int base = groups / NWARPS, ex = groups % NWARPS;
    int left = base + (warp >= NWARPS - ex ? 1 : 0);
    {
        const int o0 = (warp * base + max(warp + ex - NWARPS, 0)) * 16, o1 = o0 + left * 16;
        const uint4* lp = reinterpret_cast<const uint4*>(smem + SM_LIST + hf * (CAPS * 4) + o0);
        const char* pb = ptab + cl * 16;
        int node = __reduce_add_sync(0xffffffffu, (n0 <= o0) + (n1 <= o0) + (n2 <= o0)) - 1;
        int rem = (__reduce_min_sync(0xffffffffu, n0 > o0 ? n0 : n1 > o0 ? n1 : n2 > o0 ? n2 : total4) - o0) >> 2;
        bool head_split = !__any_sync(0xffffffffu, n0 == o0 || n1 == o0 || n2 == o0);
        const bool tail_split = o1 < total4 && !__any_sync(0xffffffffu, n0 == o1 || n1 == o1 || n2 == o1);
        uint32_t we[4], q[4];
#pragma unroll
        for (int i = 0; i < 4; i++) we[i] = half_bf16x2(reinterpret_cast<const uint32_t*>(smem + SM_WE)[(cl >> 2) * 16 + i * 4 + (cl & 3)]);
        float acc[8];
        uint32_t qa = sb + SM_Q + node * 320 + cl * 16;
        auto next_node = [&]() {
            asm volatile("ld.shared.v4.u32 {%0,%1,%2,%3}, [%4];" : "=r"(q[0]), "=r"(q[1]), "=r"(q[2]), "=r"(q[3]) : "r"(qa));
            qa += 320;
#pragma unroll
            for (int i = 0; i < 8; i++) acc[i] = 0.f;
        };
        auto store_node = [&](bool add_carry) {
            float o[4];
#pragma unroll
            for (int i = 0; i < 4; i++)
                o[i] = (hf ? acc[4 + i] : acc[i]) + __shfl_xor_sync(0xffffffffu, hf ? acc[i] : acc[4 + i], 16);
            if (add_carry) {
                int f = 0;
                for (int spin = 0; !f && spin < SPIN_MAX; spin++)
                    asm volatile("ld.acquire.cta.shared.u32 %0, [%1];" : "=r"(f) : "r"(sb + SM_FLAG + warp * 4 + 4) : "memory");
                const float4 c = *reinterpret_cast<const float4*>(smem + SM_CARRY + (threadIdx.x + 32) * 16);
                o[0] += c.x; o[1] += c.y; o[2] += c.z; o[3] += c.w;
            }
            if (head_split) {
                *reinterpret_cast<float4*>(smem + SM_CARRY + threadIdx.x * 16) = make_float4(o[0], o[1], o[2], o[3]);
                __syncwarp();
                asm volatile("st.release.cta.shared.u32 [%0], 1;" :: "r"(sb + SM_FLAG + warp * 4) : "memory");
                head_split = false;
            } else {
                asm volatile("st.shared.v2.u32 [%0], {%1,%2};" :: "r"(sb + SM_AGG + (cl >> 3) * (96 * 128) + hf * 8 + node * 128 + (((cl ^ node) & 7) << 4)),
                             "r"(pack_bf16(o[0], o[1])), "r"(pack_bf16(o[2], o[3])) : "memory");
            }
        };
        auto step = [&](uint4& p, uint32_t rec, uint32_t nxt, int d) {
            const uint32_t pv[4] = {p.x, p.y, p.z, p.w};
            uint32_t z[4];
#pragma unroll
            for (int i = 0; i < 4; i++) z[i] = fma_hi(half_hi, pv[i], fma_hi(rec, we[i], q[i]));
            p = ld_gather(pb, nxt);
#pragma unroll
            for (int i = 0; i < 4; i++) {
                acc[2 * i]     += silu_from_half(__uint_as_float(prmt(z[i], 0, 0x1044)));
                acc[2 * i + 1] += silu_from_half(bf_hi(z[i]));
            }
            if (__builtin_expect(rem == d + 1, 0)) {
                store_node(false);
                node++;
                int ns;
                asm volatile("ld.shared.u32 %0, [%1];" : "=r"(ns) : "r"(sb + SM_NSTEP + node * 4));
                rem += __reduce_max_sync(0xffffffffu, ns);
                next_node();
            }
        };
        next_node();
        __syncthreads();
        TS(5);
        uint4 ra = lp[0];
        uint4 p0 = ld_gather(pb, ra.x), p1 = ld_gather(pb, ra.y);
        if (first_round) {
            const int tid = threadIdx.x;
            const int h = tid >> 3, p = (h & 0x61) | ((h & 6) << 2) | ((h >> 2) & 6);
#pragma unroll
            for (int j = 0; j < 4; j++)
                asm volatile("cp.async.ca.shared.global [%0], [%1], 4;" :: "r"(sb + SM_W2 + p * 128 + (((((tid & 4) | j) ^ p) & 7) << 4) + (tid & 3) * 4),
                             "l"(w2 + tid * 8 + j * 2) : "memory");
            asm volatile("cp.async.commit_group;" ::: "memory");
        }
        while (left > 0) {
            const uint4 rb = lp[1];
            step(p0, ra.x, ra.z, 0); step(p1, ra.y, ra.w, 1); step(p0, ra.z, rb.x, 2); step(p1, ra.w, rb.y, 3);
            if (left == 1) break;
            ra = lp[2];
            step(p0, rb.x, rb.z, 4); step(p1, rb.y, rb.w, 5); step(p0, rb.z, ra.x, 6); step(p1, rb.w, ra.y, 7);
            lp += 2; rem -= 8; left -= 2;
        }
        if (tail_split) store_node(true);
    }
    const int rows = min(NPB, N_NODES - (int)blockIdx.x * NPB);
    const int* deg = reinterpret_cast<const int*>(smem + SM_DEG);
    const int r0 = (warp & 7) * 16 + (lane >> 2), t = lane & 3;
    float d[32];
    if (!SLOW && warp >= NWARPS - 8) {
        const float dg0 = (float)deg[min(r0, NPB)], dg1 = (float)deg[min(r0 + 8, NPB)];
#pragma unroll
        for (int J = 0; J < 2; J++) {
            const uint4 b = *reinterpret_cast<const uint4*>(smem + SM_B2 + J * 64 + t * 16);
            const uint32_t bv[4] = {b.x, b.y, b.z, b.w};
#pragma unroll
            for (int j = 0; j < 4; j++) {
                float* c = d + 16 * J + 4 * j;
                c[0] = dg0 * bf_lo(bv[j]); c[1] = dg0 * bf_hi(bv[j]); c[2] = dg1 * bf_lo(bv[j]); c[3] = dg1 * bf_hi(bv[j]);
            }
        }
#pragma unroll
        for (int i = 0; i < 32; i++) asm volatile("" : "+f"(d[i]) :: "memory");
    }
    asm volatile("cp.async.wait_group 0;" ::: "memory");
    fence_async();
    __syncthreads();
    TS(6);
    if (SLOW) {
        const int row = threadIdx.x >> 3, ch = threadIdx.x & 7;
        if (row < rows) {
            float v[8];
            float* acc = g_outacc + (blockIdx.x * NPB + row) * 64 + ch * 8;
#pragma unroll
            for (int i = 0; i < 8; i++) v[i] = first_round ? 0.f : acc[i];
            for (int k = 0; k < 128; k++) {
                const float a = bf_lo(*reinterpret_cast<const unsigned short*>(smem + SM_AGG + (k >> 6) * (96 * 128) + row * 128 + ((((k >> 3) ^ row) & 7) << 4) + (k & 7) * 2));
                const uint4 w = *reinterpret_cast<const uint4*>(smem + SM_W2 + k * 128 + (((ch ^ k) & 7) << 4));
                const uint32_t wv[4] = {w.x, w.y, w.z, w.w};
#pragma unroll
                for (int i = 0; i < 4; i++) { v[2 * i] = fmaf(a, bf_lo(wv[i]), v[2 * i]); v[2 * i + 1] = fmaf(a, bf_hi(wv[i]), v[2 * i + 1]); }
            }
#pragma unroll
            for (int q = 0; q < 4; q++) {
                const int col2 = (ch >> 2) * 16 + q * 4 + (ch & 3);
                const uint32_t bv = reinterpret_cast<const uint32_t*>(smem + SM_B2)[col2];
                if (last_round)
                    reinterpret_cast<uint32_t*>(out)[(blockIdx.x * NPB + row) * 32 + col2] =
                        pack_bf16(fmaf((float)deg[row], bf_lo(bv), v[2 * q]), fmaf((float)deg[row], bf_hi(bv), v[2 * q + 1]));
                else { acc[2 * q] = v[2 * q]; acc[2 * q + 1] = v[2 * q + 1]; }
            }
        }
    } else if (warp >= NWARPS - 8) {
        const uint64_t da = desc_sw128(sb + SM_AGG + ((warp >> 2) & 1) * 8192), db = desc_sw128(sb + SM_W2);
        wgmma_begin(d);
#pragma unroll
        for (int s = 0; s < 8; s++) wgmma_ss(d, da + (s >> 2) * (96 * 8) + (s & 3) * 2, db + s * 128, 1);
        wgmma_end(d);
        uint4* o = reinterpret_cast<uint4*>(out) + (blockIdx.x * NPB + r0) * 8 + t;
#pragma unroll
        for (int u = 0; u < 2; u++) {
#pragma unroll
            for (int J = 0; J < 2; J++) {
                const float* c = d + 16 * J + 2 * u;
                if (r0 + 8 * u < rows)
                    o[u * 64 + J * 4] = make_uint4(pack_bf16(c[0], c[1]), pack_bf16(c[4], c[5]), pack_bf16(c[8], c[9]), pack_bf16(c[12], c[13]));
            }
        }
    }
    TS(7);
}

__device__ __noinline__ void run_slow(unsigned char* smem, const char* ptab, uint32_t half_hi, const __nv_bfloat16* w2, __nv_bfloat16* out, uint32_t tag) {
    const int tid = threadIdx.x, lane = tid & 31, warp = tid >> 5;
    int* cur = reinterpret_cast<int*>(smem + SM_HIST);
    int* cnt = reinterpret_cast<int*>(smem + SM_CNT);
    const int* nst = reinterpret_cast<const int*>(smem + SM_NST);
    const uint32_t* seg = reinterpret_cast<const uint32_t*>(smem + SM_SEG);
    for (int c0 = 0; c0 < GRID;) {
        __syncthreads();
        if (tid < 160 + 96) cur[tid] = 0;
        if (tid < 32) reinterpret_cast<int*>(smem + SM_FLAG)[tid] = 0;
        int c1 = c0;
        for (int sum = 0; c1 < GRID; c1++) {
            sum += (int)(seg[c1] >> 16) - (int)(seg[c1] & 0xFFFF);
            if (sum > CAPN) break;
        }
        __syncthreads();
        for (int pass = 0; pass < 2; pass++) {
            for (int c = c0; c < c1; c++) {
                const int s = seg[c] & 0xFFFF, e = seg[c] >> 16;
                const bool wide = e - s > 256;
                if (!wide && (c & (NWARPS - 1)) != warp) continue;
                for (int i = s + (wide ? tid : lane); i < e; i += (wide ? THREADS : 32)) {
                    const uint32_t* p = reinterpret_cast<const uint32_t*>(g_rec + c * (CHUNK * 5 / 16));
                    uint32_t r, d;
                    int spin = 0;
                    do {
                        r = ld_relaxed(p + i);
                        d = ld_relaxed(p + CHUNK + (i >> 2)) ^ tag_dst(tag);
                    } while ((((r ^ tag_rec(tag)) & 0xC000u) | (d & 0x80808080u)) != 0 && ++spin < SPIN_MAX);
                    const uint32_t l = min((d >> ((i & 3) * 8)) & 0xFFu, NPB - 1u);
                    if (pass == 0) atomicAdd(&cnt[l], 2);
                    else put_rec(smem, nst[l] + atomicAdd(&cur[l], 2), r);
                }
            }
            __syncthreads();
            if (pass == 0) {
                if (warp == 0) scan_nodes(smem, lane);
                __syncthreads();
            }
        }
        run_round<true>(smem, ptab, half_hi, w2, out, c0 == 0, c1 >= GRID);
        c0 = c1;
    }
}

template <int PHASES>
__global__ void __launch_bounds__(THREADS, 1)
mpnn_kernel(const __nv_bfloat16* __restrict__ x, const unsigned short* __restrict__ e_attr,
            const int* __restrict__ src, const int* __restrict__ dst,
            const __nv_bfloat16* __restrict__ w1, const void* __restrict__ b1,
            const __nv_bfloat16* __restrict__ w2, const void* __restrict__ b2,
            __nv_bfloat16* __restrict__ out, const char* __restrict__ ptab, uint32_t half_hi) {
    if (PHASES == 4) { if (threadIdx.x == 0) g_epoch[0] = g_epoch[0] + 1; return; }
    extern __shared__ __align__(1024) unsigned char smem[];
    const uint32_t sb = (uint32_t)__cvta_generic_to_shared(smem);
    const int tid = threadIdx.x, lane = tid & 31;
    const int warp = __shfl_sync(0xffffffffu, tid >> 5, 0);
    const int cta = blockIdx.x;
    int* hist = reinterpret_cast<int*>(smem + SM_HIST);
    TS(0);

    if ((PHASES & 1) && tid == THREADS - 1) {
        asm volatile("mbarrier.init.shared::cta.b64 [%0], 1;" :: "r"(sb + SM_MBAR) : "memory");
        asm volatile("fence.mbarrier_init.release.cluster;" ::: "memory");
    }
    uint2 vd[EIT];
    const int e0 = cta * CHUNK + tid * 2;
    const bool tail_ok = tid * 2 + (EIT - 1) * THREADS * 2 < CHUNK && e0 + (EIT - 1) * THREADS * 2 < N_EDGES;
    auto my_tab = [&]() { return &g_tab[((threadIdx.x >> 1) * GRID + blockIdx.x) * 2 + (threadIdx.x & 1)]; };
    if (PHASES & 1) {
        vd[EIT - 1] = make_uint2(0, 0);
#pragma unroll
        for (int j = 0; j < EIT; j++) if (j < EIT - 1 || tail_ok) vd[j] = ld_stream2(dst + e0 + j * THREADS * 2);
    }
    if (tid < 160 + 96 + 96 + 32) hist[tid] = tid == 140 ? 44151 : 0;
    uint32_t vb1 = 0;
    if (warp >= 26 && warp <= 28) vb1 = ld_stream1(warp == 28 ? g_epoch : reinterpret_cast<const uint32_t*>(b1) + (tid & 63));
    if (PHASES & 1) {
        __syncthreads();
        if (tid == THREADS - 1) {
            const int n = min(CHUNK, N_EDGES - cta * CHUNK);
            asm volatile("mbarrier.arrive.expect_tx.shared::cta.b64 _, [%0], %1;" :: "r"(sb + SM_MBAR), "r"(n * 6) : "memory");
            asm volatile("cp.async.bulk.shared::cluster.global.mbarrier::complete_tx::bytes [%0], [%1], %2, [%3];"
                         :: "r"(sb + SM_SRC), "l"(src + cta * CHUNK), "r"(n * 4), "r"(sb + SM_MBAR) : "memory");
            asm volatile("cp.async.bulk.shared::cluster.global.mbarrier::complete_tx::bytes [%0], [%1], %2, [%3];"
                         :: "r"(sb + SM_E), "l"(e_attr + cta * CHUNK), "r"(n * 2), "r"(sb + SM_MBAR) : "memory");
        }
    }
    if (PHASES == 3 && tid < GRID * 2) st_relaxed(my_tab(), make_uint4(0, 0, 0, 0));
    auto owner = [](uint32_t v) { return ((v & 16383u) * 44151u) >> 22; };
    if (PHASES & 1) {
        const uint32_t mul = hist[140];
#pragma unroll
        for (int j = 0; j < EIT; j++) {
            if (j < EIT - 1 || tail_ok) {
                const uint32_t r0 = atomicAdd(&hist[(vd[j].x * mul) >> 22], 1 << 14), r1 = atomicAdd(&hist[(vd[j].y * mul) >> 22], 1 << 14);
                vd[j].x |= r0; vd[j].y |= r1;
            }
        }
    }
    {
        const uint32_t dw = sb + SM_W1 + ((tid >> 3) & 1) * 8192 + (tid >> 4) * 128 + (((tid ^ (tid >> 4)) & 7) << 4);
        if (tid < 96 * 8) cp16(sb + SM_X + (tid >> 3) * 128 + (((tid ^ (tid >> 3)) & 7) << 4), x + min(cta * (NPB * 64) + tid * 8, N_NODES * 64 - 8));
        else if (tid < 96 * 8 + 24) {
            const int i = tid - 96 * 8;
            cp16(sb + SM_WE + i * 16, (i < 16 ? reinterpret_cast<const char*>(w1 + 128 * 128) : reinterpret_cast<const char*>(b2) - 256) + i * 16);
        }
        cp16(dw, w1 + tid * 8);
        cp16(dw + 16384, w1 + tid * 8 + 64 * 128);
        asm volatile("cp.async.commit_group;" ::: "memory");
    }
    if (warp >> 1 == 13)
        *reinterpret_cast<float2*>(smem + SM_B1 + (warp & 1) * 256 + (lane & 3) * 64 + (lane >> 2) * 8) = make_float2(0.5f * bf_lo(vb1), 0.5f * bf_hi(vb1));
    if (warp == 28) *reinterpret_cast<unsigned*>(smem + SM_EPOCH) = vb1;
    __syncthreads();
    TS(2);
    if ((PHASES & 1) && warp == NWARPS - 1) {
        int h[5], s = 0;
#pragma unroll
        for (int q = 0; q < 5; q++) { h[q] = hist[lane * 5 + q]; s += h[q]; }
        int inc = s;
#pragma unroll
        for (int o = 1; o < 32; o <<= 1) {
            const int v = __shfl_up_sync(0xffffffffu, inc, o);
            if (lane >= o) inc += v;
        }
        inc -= s;
#pragma unroll
        for (int q = 0; q < 5; q++) { hist[lane * 5 + q] = inc; inc += h[q]; }
    }

    const unsigned epoch = *reinterpret_cast<const unsigned*>(smem + SM_EPOCH);
    const uint32_t tag = ((epoch & 0xFFFFu) + 1u) << 14;

    if (PHASES & 1) {
        __syncthreads();
        TS(9);
        unsigned char* stage = smem + SM_STAGE;
#pragma unroll
        for (int j = 0; j < EIT; j++) {
            const uint32_t o0 = owner(vd[j].x), o1 = owner(vd[j].y);
            vd[j].x += hist[o0] - o0 * NPB + (tag_dst(tag) & 0x80u);
            vd[j].y += hist[o1] - o1 * NPB + (tag_dst(tag) & 0x80u);
        }
        uint32_t ok = 0;
        for (int spin = 0; !ok && spin < SPIN_MAX; spin++)
            asm volatile("{.reg .pred p; mbarrier.try_wait.parity.shared::cta.b64 p, [%1], 0; selp.u32 %0, 1, 0, p;}"
                         : "=r"(ok) : "r"(sb + SM_MBAR) : "memory");
#pragma unroll
        for (int j = 0; j < EIT; j++) {
            if (j < EIT - 1 || tail_ok) {
                const uint2 vs = *reinterpret_cast<const uint2*>(smem + SM_SRC + (j * THREADS + tid) * 8);
                const uint32_t ve = *reinterpret_cast<const uint32_t*>(smem + SM_E + (j * THREADS + tid) * 4);
                *reinterpret_cast<uint32_t*>(stage + (vd[j].x >> 12)) = prmt(vs.x | tag_rec(tag), ve, 0x5410);
                *reinterpret_cast<uint32_t*>(stage + (vd[j].y >> 12)) = prmt(vs.y | tag_rec(tag), ve, 0x7610);
                stage[CHUNK * 4 + (vd[j].x >> 14)] = (unsigned char)vd[j].x;
                stage[CHUNK * 4 + (vd[j].y >> 14)] = (unsigned char)vd[j].y;
            }
        }
    }
    asm volatile("cp.async.wait_group 0;" ::: "memory");
    fence_async();
    __syncthreads();
    TS(10);
    if (PHASES & 1) {
        const unsigned char* stage = smem + SM_STAGE;
#pragma unroll
        for (int j = 0; j < 2; j++)
            if (j == 0 || THREADS + tid < CHUNK * 5 / 16)
                st_relaxed(g_rec + cta * (CHUNK * 5 / 16) + j * THREADS + tid, *reinterpret_cast<const uint4*>(stage + (j * THREADS + tid) * 16));
        __syncthreads();
        if (tid < GRID * 2) {
            const uint32_t se = (hist[tid >> 1] >> 14) | (hist[(tid >> 1) + 1] << 2);
            st_relaxed(my_tab(), make_uint4(se, tag, se, tag));
        }
        TS(3);
    }

    {
        const int nq = warp >> 3, g = lane >> 2, t = lane & 3;
        const int r0 = (warp & 7) * 16 + g;
        float d[32];
        const uint64_t da = desc_sw128(sb + SM_X + ((warp >> 2) & 1) * 8192), db = desc_sw128(sb + SM_W1 + nq * 8192);
        asm volatile("wgmma.fence.sync.aligned;" ::: "memory");
#pragma unroll
        for (int s = 0; s < 4; s++) wgmma_ss(d, da + s * 2, db + s * 128, s);
        wgmma_end(d);
        if ((warp & 7) < 6) {
            if (nq >= 2) {
#pragma unroll
                for (int j = 0; j < 4; j++) {
                    const float4 b = *reinterpret_cast<const float4*>(smem + SM_B1 + (nq & 1) * 256 + t * 64 + j * 16);
                    float* c = d + 8 * j;
                    c[0] = fmaf(c[0], 0.5f, b.x); c[1] = fmaf(c[1], 0.5f, b.y); c[2] = fmaf(c[2], 0.5f, b.x); c[3] = fmaf(c[3], 0.5f, b.y);
                    c[4] = fmaf(c[4], 0.5f, b.z); c[5] = fmaf(c[5], 0.5f, b.w); c[6] = fmaf(c[6], 0.5f, b.z); c[7] = fmaf(c[7], 0.5f, b.w);
                }
            }
            const int pitch = nq >= 2 ? 320 : 256;
            unsigned char* o = smem + (nq >= 2 ? SM_Q : SM_SRC) + r0 * pitch + (nq & 1) * 128 + t * 16;
#pragma unroll
            for (int u = 0; u < 2; u++) {
#pragma unroll
                for (int J = 0; J < 2; J++) {
                    const float* c = d + 16 * J + 2 * u;
                    *reinterpret_cast<uint4*>(o + u * 8 * pitch + J * 64) =
                        make_uint4(pack_bf16(c[0], c[1]), pack_bf16(c[4], c[5]), pack_bf16(c[8], c[9]), pack_bf16(c[12], c[13]));
                }
            }
        }
        if ((PHASES & 1) && cta == 0 && tid < 16) g_P[N_NODES * 16 + tid] = make_uint4(0xF149F149u, 0xF149F149u, 0xF149F149u, 0xF149F149u);
    }
    if (PHASES & 1) {
        if (warp < 16) { fence_async(); asm volatile("bar.arrive 1, 544;" ::: "memory"); }
        if (warp == NWARPS - 1) {
            asm volatile("bar.sync 1, 544;" ::: "memory");
            if (lane == 0) {
                asm volatile("cp.async.bulk.global.shared::cta.bulk_group [%0], [%1], %2;"
                             :: "l"(g_P + cta * NPB * 16), "r"(sb + SM_SRC), "r"(min(NPB, N_NODES - cta * NPB) * 256) : "memory");
                asm volatile("cp.async.bulk.commit_group;" ::: "memory");
                asm volatile("cp.async.bulk.wait_group 0;" ::: "memory");
                asm volatile("fence.proxy.async.global;" ::: "memory");
                if (PHASES == 3) asm volatile("red.release.gpu.global.add.u32 [%0], 1;" :: "l"(&g_pcnt) : "memory");
            }
        }
    }
    TS(1);
    if (!(PHASES & 2)) return;

    const int c = tid / LPC, j = tid - c * LPC;
    int s = 0, e = 0;
    if (c < GRID) {
        const uint2* tp = reinterpret_cast<const uint2*>(&g_tab[(cta * GRID + c) * 2]);
        uint2 v = ld_relaxed(tp);
        for (int spin = 0; v.y != tag && spin < SPIN_MAX; spin++) v = ld_relaxed(tp);
        if (v.y != tag) v.x = 0;
        s = v.x & 0xFFFF; e = v.x >> 16;
        reinterpret_cast<uint32_t*>(smem + SM_SEG)[c] = v.x;
    }
    TS(11);
    const int nquad = ((e + 3) >> 2) - (s >> 2) - j;
    const uint4* rp = g_rec + c * (CHUNK * 5 / 16) + (s >> 2) + j;
    const uint32_t* dp = reinterpret_cast<const uint32_t*>(g_rec + c * (CHUNK * 5 / 16)) + CHUNK + (s >> 2) + j;
    const int kmax = __reduce_max_sync(0xffffffffu, nquad);
    uint4 r[RIT];
    uint32_t dl[RIT], y[RIT * 4], rk[RIT * 4];
    for (int spin = 0; spin < SPIN_MAX; spin++) {
        const uint32_t t = tag_rec(tag);
        uint32_t bad = 0, badd = 0;
#pragma unroll
        for (int k = 0; k < RIT; k++) {
            r[k] = make_uint4(t, t, t, t); dl[k] = tag_dst(tag);
            if (k * LPC < nquad) { r[k] = ld_relaxed(rp + k * LPC); dl[k] = ld_relaxed(dp + k * LPC); }
        }
#pragma unroll
        for (int k = 0; k < RIT; k++) {
            bad |= (r[k].x ^ t) | (r[k].y ^ t) | (r[k].z ^ t) | (r[k].w ^ t);
            dl[k] ^= tag_dst(tag);
            badd |= dl[k];
        }
        if (((bad & 0xC000u) | (badd & 0x80808080u)) == 0) break;
    }
    TS(12);
#pragma unroll
    for (int k = 0; k < RIT; k++) {
        if (k < RIT - 1 || k * LPC < kmax) {
#pragma unroll
            for (int i = 0; i < 4; i++) {
                const bool mine = (uint32_t)(j * 4 - (s & 3) + k * LPC * 4 + i) < (uint32_t)(e - s);
                y[4 * k + i] = prmt(dl[k], NPB, mine ? 0x7770 + i : 0x7774) * 4;
                asm volatile("{.reg .pred p; setp.lt.u32 p, %1, %3; @p atom.shared.add.u32 %0, [%2], 2;}"
                             : "=r"(rk[4 * k + i]) : "r"(y[4 * k + i]), "r"(sb + SM_CNT + y[4 * k + i]), "n"(4 * NPB) : "memory");
            }
        }
    }
    auto acquire_p = [&]() {
        if (PHASES == 3 && tid == THREADS - 32) {
            const unsigned target = (epoch + 1u) * GRID;
            unsigned v;
            int spin = 0;
            do {
                asm volatile("ld.acquire.gpu.global.u32 %0, [%1];" : "=r"(v) : "l"(&g_pcnt) : "memory");
            } while ((int)(v - target) < 0 && ++spin < SPIN_MAX);
            if (cta == 0) g_epoch[0] = epoch + 1u;
        }
    };
    if (warp != NWARPS - 1) {
        uint32_t slow;
        asm volatile("{.reg .pred p, q; setp.gt.s32 p, %1, %2; bar.red.or.pred q, 2, %3, p; selp.u32 %0, 1, 0, q;}"
                     : "=r"(slow) : "r"(nquad + j), "n"(LPC * RIT), "n"(THREADS - 32) : "memory");
        TS(4);
        if (warp == 0) {
            if (!slow) scan_nodes(smem, lane);
            *reinterpret_cast<uint32_t*>(smem + SM_EPOCH + 4) = slow;
        }
    }
    __syncthreads();
    acquire_p();
    if (*reinterpret_cast<const uint32_t*>(smem + SM_EPOCH + 4)) {
        run_slow(smem, ptab, half_hi, w2, out, tag);
        return;
    }
#pragma unroll
    for (int k = 0; k < RIT; k++) {
        if (k < RIT - 1 || k * LPC < kmax) {
            const uint32_t rv[4] = {r[k].x, r[k].y, r[k].z, r[k].w};
#pragma unroll
            for (int i = 0; i < 4; i++) rk[4 * k + i] += *reinterpret_cast<const int*>(smem + SM_NST + y[4 * k + i]);
#pragma unroll
            for (int i = 0; i < 4; i++) if (y[4 * k + i] < 4 * NPB) put_rec(smem, rk[4 * k + i], rv[i]);
        }
    }
    run_round<false>(smem, ptab, half_hi, w2, out, true, true);
}

}

extern "C" void kernel_launch(void* const* d_in, const int* in_sizes, int n_in, void* d_out, int out_size) {
    (void)in_sizes; (void)n_in; (void)out_size;
    const __nv_bfloat16* x  = (const __nv_bfloat16*)d_in[0];
    const unsigned short* e = (const unsigned short*)d_in[1];
    const int* src          = (const int*)d_in[2];
    const int* dst          = (const int*)d_in[3];
    const __nv_bfloat16* w1 = (const __nv_bfloat16*)d_in[4];
    const void* b1          = d_in[5];
    const __nv_bfloat16* w2 = (const __nv_bfloat16*)d_in[6];
    const void* b2          = d_in[7];
    __nv_bfloat16* out = (__nv_bfloat16*)d_out;

    static int fused = -1;
    static void* ptab = nullptr;
    if (fused < 0) {
        cudaFuncSetAttribute(mpnn_kernel<3>, cudaFuncAttributeMaxDynamicSharedMemorySize, SM_TOTAL);
        cudaFuncSetAttribute(mpnn_kernel<1>, cudaFuncAttributeMaxDynamicSharedMemorySize, SM_TOTAL);
        cudaFuncSetAttribute(mpnn_kernel<2>, cudaFuncAttributeMaxDynamicSharedMemorySize, SM_TOTAL);
        cudaGetSymbolAddress(&ptab, g_P);
        int dev = 0, sms = 0, per_sm = 0;
        cudaGetDevice(&dev);
        cudaDeviceGetAttribute(&sms, cudaDevAttrMultiProcessorCount, dev);
        cudaOccupancyMaxActiveBlocksPerMultiprocessor(&per_sm, mpnn_kernel<3>, THREADS, SM_TOTAL);
        fused = (sms * per_sm >= GRID) ? 1 : 0;
    }
    const char* pt = (const char*)ptab;
    if (fused) {
        mpnn_kernel<3><<<GRID, THREADS, SM_TOTAL>>>(x, e, src, dst, w1, b1, w2, b2, out, pt, 0x3F000000u);
    } else {
        mpnn_kernel<1><<<GRID, THREADS, SM_TOTAL>>>(x, e, src, dst, w1, b1, w2, b2, out, pt, 0x3F000000u);
        mpnn_kernel<2><<<GRID, THREADS, SM_TOTAL>>>(x, e, src, dst, w1, b1, w2, b2, out, pt, 0x3F000000u);
        mpnn_kernel<4><<<1, 32>>>(x, e, src, dst, w1, b1, w2, b2, out, pt, 0x3F000000u);
    }
}
```
